```python
import torch

def _softmax(x, axis=-1):
    return torch.softmax(x, dim=axis)
def _gelu(x):
    return torch.nn.functional.gelu(x, approximate="tanh")
def _silu(x):
    return torch.nn.functional.silu(x)
def _sigmoid(x):
    return torch.sigmoid(x)
def _layernorm(x, axis=-1, eps=1e-5):
    m = x.mean(dim=axis, keepdim=True)
    v = x.var(dim=axis, keepdim=True, unbiased=False)
    return (x - m) / torch.sqrt(v + eps)
def _scatter_add(tgt, idx, src, axis=0):
    return tgt.clone().index_add_(axis, idx, src)
def _segment_sum(src, seg, n):
    out = torch.zeros((n,) + src.shape[1:], dtype=src.dtype)
    return out.index_add_(0, seg, src)
def _pad(x, pw):
    flat = tuple(v for pair in reversed(pw) for v in pair)
    return torch.nn.functional.pad(x, flat)

kernel_name = 'sequential_preLN__gqa_block_cached__glu_gated_geglu__decode'

def setup_inputs():

    _w = (lambda a: (lambda t: t.to(torch.bfloat16) if t.is_floating_point() else t)(torch.as_tensor(a)))
    def _A_setup():
        B, Sq, D = 1, 1, 640
        Hq, Hkv, Sk, Dh = 32, 32, 4096, 128
        assert Hq % Hkv == 0, (Hq, Hkv)
        return {
            "x": _w((lambda *s: torch.randn(*s, dtype=torch.bfloat16) * 0.05)(B, Sq, D)),
            "k_cache": _w((lambda *s: torch.randn(*s, dtype=torch.bfloat16) * 1.6)(B, Hkv, Sk, Dh)),
            "v_cache": _w((lambda *s: torch.randn(*s, dtype=torch.bfloat16) * 0.8)(B, Hkv, Sk, Dh)),
            "wq": _w((lambda *s: torch.randn(*s, dtype=torch.bfloat16) * 1.6)(D, Hq * Dh) * (D ** -0.5)),
            "wo": _w((lambda *s: torch.randn(*s, dtype=torch.bfloat16) * 0.8)(Hq * Dh, D) * ((Hq * Dh) ** -0.5)),
        }
    _A_in = _A_setup()

    def _B_setup():
        B, S, Dm, Df = 1, 1, 640, 1728
        return {
            "x": _w((lambda *s: torch.randn(*s, dtype=torch.bfloat16) * 0.05)(B, S, Dm)),
            "w_gate": _w((lambda *s: torch.randn(*s, dtype=torch.bfloat16) * 0.4)(Dm, Df) * (Dm ** -0.5)),
            "w_up": _w((lambda *s: torch.randn(*s, dtype=torch.bfloat16) * 0.4)(Dm, Df) * (Dm ** -0.5)),
            "w_down": _w((lambda *s: torch.randn(*s, dtype=torch.bfloat16) * 0.4)(Df, Dm) * (Df ** -0.5)),
        }
    _B_in = _B_setup()

    return {
        "A_x": _A_in["x"],
        "A_k_cache": _A_in["k_cache"],
        "A_v_cache": _A_in["v_cache"],
        "A_wq": _A_in["wq"],
        "A_wo": _A_in["wo"],
        "B_x": _B_in["x"],
        "B_w_gate": _B_in["w_gate"],
        "B_w_up": _B_in["w_up"],
        "B_w_down": _B_in["w_down"],
    }

def reference(A_x, A_k_cache, A_v_cache, A_wq, A_wo, B_x, B_w_gate, B_w_up, B_w_down):
    def _A_ref(x, k_cache, v_cache, wq, wo):
        B, Sq, D = x.shape
        Hq, Dh = 32, 128
        Hkv = k_cache.shape[1]
        rep = Hq // Hkv
        q = (lambda x, *d: x.permute(*d))((x @ wq).reshape(B, Sq, Hq, Dh), 0, 2, 1, 3)
        k = (lambda x, n, axis: torch.repeat_interleave(x, n, dim=axis))(k_cache, rep, axis=1)
        v = (lambda x, n, axis: torch.repeat_interleave(x, n, dim=axis))(v_cache, rep, axis=1)
        scores = torch.einsum("bhqd,bhkd->bhqk", q, k) * (Dh ** -0.5)
        p = _softmax(scores, axis=-1)
        o = torch.einsum("bhqk,bhkd->bhqd", p, v)
        return (lambda x, *d: x.permute(*d))(o, 0, 2, 1, 3).reshape(B, Sq, Hq * Dh) @ wo

    def _B_ref(x, w_gate, w_up, w_down):
        g = torch.einsum("bsd,df->bsf", x, w_gate)
        u = torch.einsum("bsd,df->bsf", x, w_up)
        h = _gelu(g) * u
        return torch.einsum("bsf,fd->bsd", h, w_down)

    x = A_x
    h = x + _A_ref(_layernorm(x, axis=-1), A_k_cache, A_v_cache, A_wq, A_wo)
    h2 = h + _B_ref(_layernorm(h, axis=-1), B_w_gate, B_w_up, B_w_down)
    return h2
```

```cpp
#include <cuda_runtime.h>
#include <cuda_bf16.h>
#include <cuda.h>
#include <stdint.h>

namespace {

constexpr int DM = 640, HQ = 32, DH = 128, SK = 4096, DF = 1728;
constexpr int NCTA = 128;
constexpr int NFFN = DF / 16;
constexpr int NCOMP = 320;
constexpr int NTHREADS = 352;
constexpr int TILE_BYTES = 16384;
constexpr int NSLOT = 12;
constexpr int NKT = 16, NVT = 16;
constexpr int SPIN_LIMIT = 1 << 22;

#define JW 6
#define JG 12

struct __align__(1024) Smem {
    uint8_t  ring[NSLOT][TILE_BYTES];
    float    p[SK];
    float    xn[DM + 64];
    float    part[10][128];
    float    q[DH];
    float    wloc[10][80];
    float    stat[32];
    uint16_t sc[1024];
    uint64_t full[NSLOT];
    uint64_t empty[NSLOT];
};

__device__ float    g_qpart[NCTA * DH];
__device__ uint4    g_scores[NCTA * 128];
__device__ uint4    g_qflag[HQ * 2];
__device__ uint4    g_sflag[HQ * 2];
__device__ float4   g_acc1[160 * 16];
__device__ float4   g_acc2[160 * 16];
#define TS(i)

__device__ __forceinline__ uint32_t s2u(const void* p) { return (uint32_t)__cvta_generic_to_shared(p); }
__device__ __forceinline__ void mbar_init(uint32_t bar, int cnt) {
    asm volatile("mbarrier.init.shared::cta.b64 [%0], %1;" ::"r"(bar), "r"(cnt) : "memory");
}
__device__ __forceinline__ void mbar_expect(uint32_t bar, uint32_t bytes) {
    asm volatile("mbarrier.arrive.expect_tx.shared::cta.b64 _, [%0], %1;" ::"r"(bar), "r"(bytes) : "memory");
}
__device__ __forceinline__ void mbar_arrive(uint32_t bar) {
    asm volatile("mbarrier.arrive.shared::cta.b64 _, [%0];" ::"r"(bar) : "memory");
}
__device__ __forceinline__ void mbar_wait(uint32_t bar, uint32_t par) {
    uint32_t ok;
    int n = 0;
    do {
        asm volatile("{\n .reg .pred p;\n mbarrier.try_wait.parity.shared::cta.b64 p, [%1], %2;\n selp.u32 %0, 1, 0, p;\n}"
                     : "=r"(ok) : "r"(bar), "r"(par) : "memory");
        if (++n > SPIN_LIMIT) __trap();
    } while (!ok);
}
__device__ __forceinline__ void bulk_load(uint32_t dst, const void* src, uint32_t bytes, uint32_t bar) {
    asm volatile("cp.async.bulk.shared::cluster.global.mbarrier::complete_tx::bytes [%0], [%1], %2, [%3];"
                 ::"r"(dst), "l"(src), "r"(bytes), "r"(bar) : "memory");
}
__device__ __forceinline__ void tma_2d(uint32_t dst, const CUtensorMap* m, int c0, int c1, uint32_t bar) {
    asm volatile("cp.async.bulk.tensor.2d.shared::cluster.global.mbarrier::complete_tx::bytes [%0], [%1, {%3, %4}], [%2];"
                 ::"r"(dst), "l"(m), "r"(bar), "r"(c0), "r"(c1) : "memory");
}
__device__ __forceinline__ void bar_sync(int id, int n) { asm volatile("bar.sync %0, %1;" ::"r"(id), "r"(n) : "memory"); }
__device__ __forceinline__ uint4 ldg128(const void* p) {
    uint4 v;
    asm volatile("ld.global.nc.L1::no_allocate.v4.u32 {%0,%1,%2,%3}, [%4];" : "=r"(v.x), "=r"(v.y), "=r"(v.z), "=r"(v.w) : "l"(p));
    return v;
}
__device__ __forceinline__ uint32_t ldg32(const void* p) {
    uint32_t v;
    asm volatile("ld.global.nc.L1::no_allocate.u32 %0, [%1];" : "=r"(v) : "l"(p));
    return v;
}
__device__ __forceinline__ uint32_t ldg32_pf256(const void* p) {
    uint32_t v;
    asm volatile("ld.global.nc.L1::no_allocate.L2::256B.u32 %0, [%1];" : "=r"(v) : "l"(p));
    return v;
}
__device__ __forceinline__ uint4 ld_rlx128(const void* p) {
    uint4 v;
    asm volatile("ld.relaxed.gpu.global.v4.u32 {%0,%1,%2,%3}, [%4];" : "=r"(v.x), "=r"(v.y), "=r"(v.z), "=r"(v.w) : "l"(p) : "memory");
    return v;
}
__device__ __forceinline__ float ld_rlx32f(const void* p) {
    float v;
    asm volatile("ld.relaxed.gpu.global.f32 %0, [%1];" : "=f"(v) : "l"(p) : "memory");
    return v;
}
__device__ __forceinline__ void st_rlx128(void* p, uint4 v) {
    asm volatile("st.relaxed.gpu.global.v4.u32 [%0], {%1,%2,%3,%4};" ::"l"(p), "r"(v.x), "r"(v.y), "r"(v.z), "r"(v.w) : "memory");
}
__device__ __forceinline__ void st_rlx32(void* p, uint32_t v) {
    asm volatile("st.relaxed.gpu.global.u32 [%0], %1;" ::"l"(p), "r"(v) : "memory");
}
__device__ __forceinline__ void red_v4(void* p, float a, float b, float c, float d) {
    asm volatile("red.relaxed.gpu.global.add.v4.f32 [%0], {%1,%2,%3,%4};" ::"l"(p), "f"(a), "f"(b), "f"(c), "f"(d) : "memory");
}
__device__ __forceinline__ float4 atom_v4(void* p, float a, float b, float c, float d) {
    float4 r;
    asm volatile("atom.relaxed.gpu.global.add.v4.f32 {%0,%1,%2,%3}, [%4], {%5,%6,%7,%8};"
                 : "=f"(r.x), "=f"(r.y), "=f"(r.z), "=f"(r.w) : "l"(p), "f"(a), "f"(b), "f"(c), "f"(d) : "memory");
    return r;
}
__device__ __forceinline__ float bf_lo(uint32_t v) { return __uint_as_float(v << 16); }
__device__ __forceinline__ float bf_hi(uint32_t v) { return __uint_as_float(v & 0xffff0000u); }
__device__ __forceinline__ float rbf(float v) { return __bfloat162float(__float2bfloat16_rn(v)); }

__device__ __forceinline__ void wait_flags(const uint4* f) {
    int n = 0;
    while (true) {
        uint4 v = ld_rlx128(f);
        if (v.x & v.y & v.z & v.w) break;
        if (++n > SPIN_LIMIT) __trap();
        __nanosleep(40);
    }
    __threadfence();
}

__device__ __forceinline__ void layernorm2(float a0, float a1, float* stat, int w, int lane, float& o0, float& o1) {
    const float piv = __shfl_sync(0xffffffffu, a0, 0);
    const float d0 = a0 - piv, d1 = a1 - piv;
    float s1 = d0 + d1, s2 = d0 * d0 + d1 * d1;
#pragma unroll
    for (int o = 16; o > 0; o >>= 1) {
        s1 += __shfl_xor_sync(0xffffffffu, s1, o);
        s2 += __shfl_xor_sync(0xffffffffu, s2, o);
    }
    if (lane == 0) {
        const float mu = s1 * (1.0f / 64.0f);
        *reinterpret_cast<float2*>(stat + 2 * w) = make_float2(piv + mu, fmaxf(s2 - s1 * mu, 0.0f));
    }
    bar_sync(1, NCOMP);
    float mw[10], ms = 0.f, m2 = 0.f;
#pragma unroll
    for (int i = 0; i < 5; i++) {
        const float4 v = *reinterpret_cast<const float4*>(stat + 4 * i);
        mw[2 * i] = v.x; mw[2 * i + 1] = v.z;
        ms += v.x + v.z; m2 += v.y + v.w;
    }
    const float mean = ms * 0.1f;
    float dv = 0.f;
#pragma unroll
    for (int i = 0; i < 10; i++) { const float d = mw[i] - mean; dv = fmaf(d, d, dv); }
    const float var = (m2 + 64.0f * dv) * (1.0f / 640.0f);
    const float mb = rbf(mean);
    const float den = rbf(sqrtf(rbf(rbf(var) + 1e-5f)));
    o0 = rbf(__fdiv_rn(rbf(a0 - mb), den));
    o1 = rbf(__fdiv_rn(rbf(a1 - mb), den));
}

__global__ void __launch_bounds__(NTHREADS, 1)
fused_block_kernel(const __nv_bfloat16* __restrict__ x, const __nv_bfloat16* __restrict__ kc,
                   const __grid_constant__ CUtensorMap vmap, const __nv_bfloat16* __restrict__ wq,
                   const __nv_bfloat16* __restrict__ wo, const __nv_bfloat16* __restrict__ wg,
                   const __nv_bfloat16* __restrict__ wu, const __nv_bfloat16* __restrict__ wd,
                   __nv_bfloat16* __restrict__ out) {
    extern __shared__ __align__(1024) uint8_t smem_raw[];
    Smem& sm = *reinterpret_cast<Smem*>(smem_raw);
    const int t = threadIdx.x, w = t >> 5, lane = t & 31;
    const int cta = blockIdx.x, h = cta >> 2, s = cta & 3;

    if (w == 10) {
        if (lane == 0) {
            for (int i = 0; i < NSLOT; i++) { mbar_init(s2u(&sm.full[i]), 1); mbar_init(s2u(&sm.empty[i]), 8); }
            asm volatile("fence.mbarrier_init.release.cluster;" ::: "memory");
            const uint8_t* kbase = reinterpret_cast<const uint8_t*>(kc) + (size_t)cta * (NKT * TILE_BYTES);
#pragma unroll 1
            for (int i = 0; i < NSLOT; i++) {
                mbar_expect(s2u(&sm.full[i]), TILE_BYTES);
                bulk_load(s2u(sm.ring[i]), kbase + (size_t)i * TILE_BYTES, TILE_BYTES, s2u(&sm.full[i]));
            }
            asm volatile("prefetch.tensormap [%0];" ::"l"(&vmap) : "memory");
        }
        __syncthreads();
        if (lane == 0) {
            const uint8_t* kbase = reinterpret_cast<const uint8_t*>(kc) + (size_t)cta * (NKT * TILE_BYTES);
#pragma unroll 1
            for (int i = NSLOT; i < NKT + NVT; i++) {
                const int sl = i % NSLOT;
                mbar_wait(s2u(&sm.empty[sl]), ((i / NSLOT) - 1) & 1);
                mbar_expect(s2u(&sm.full[sl]), TILE_BYTES);
                if (i < NKT) bulk_load(s2u(sm.ring[sl]), kbase + (size_t)i * TILE_BYTES, TILE_BYTES, s2u(&sm.full[sl]));
                else tma_2d(s2u(sm.ring[sl]), &vmap, s * 32, h * SK + (i - NKT) * 256, s2u(&sm.full[sl]));
            }
        }
        return;
    }

    TS(0);
    const size_t slot_off = (size_t)(t >> 1) * 16 + (t & 1);
    uint4 wqr[8];
    {
        const __nv_bfloat16* b = wq + (size_t)(s * 160 + 2 * w + (lane >> 4)) * (HQ * DH) + h * DH + (lane & 15) * 8;
#pragma unroll
        for (int i = 0; i < 8; i++) wqr[i] = ldg128(b + (size_t)i * 20 * (HQ * DH));
    }
    const uint32_t xraw = ldg32(x + 2 * t);
    if (cta == NCTA - 1) st_rlx128(&g_acc2[slot_off], make_uint4(0, 0, 0, 0));
    __syncthreads();
    const float x0 = bf_lo(xraw), x1 = bf_hi(xraw);
    {
        float n0, n1;
        layernorm2(x0, x1, sm.stat, w, lane, n0, n1);
        *reinterpret_cast<float2*>(sm.xn + 2 * t) = make_float2(n0, n1);
        bar_sync(1, NCOMP);
        float a[8];
#pragma unroll
        for (int j = 0; j < 8; j++) a[j] = 0.f;
#pragma unroll
        for (int i = 0; i < 8; i++) {
            const float xv = sm.xn[s * 160 + 20 * i + 2 * w + (lane >> 4)];
            a[0] = fmaf(xv, bf_lo(wqr[i].x), a[0]); a[1] = fmaf(xv, bf_hi(wqr[i].x), a[1]);
            a[2] = fmaf(xv, bf_lo(wqr[i].y), a[2]); a[3] = fmaf(xv, bf_hi(wqr[i].y), a[3]);
            a[4] = fmaf(xv, bf_lo(wqr[i].z), a[4]); a[5] = fmaf(xv, bf_hi(wqr[i].z), a[5]);
            a[6] = fmaf(xv, bf_lo(wqr[i].w), a[6]); a[7] = fmaf(xv, bf_hi(wqr[i].w), a[7]);
        }
#pragma unroll
        for (int j = 0; j < 8; j++) a[j] += __shfl_xor_sync(0xffffffffu, a[j], 16);
        if (lane < 16) {
            *reinterpret_cast<float4*>(&sm.part[w][lane * 8]) = make_float4(a[0], a[1], a[2], a[3]);
            *reinterpret_cast<float4*>(&sm.part[w][lane * 8 + 4]) = make_float4(a[4], a[5], a[6], a[7]);
        }
        bar_sync(1, NCOMP);
        if (t < DH) {
            float v = 0.f;
#pragma unroll
            for (int i = 0; i < 10; i++) v += sm.part[i][t];
            st_rlx32(&g_qpart[cta * DH + t], __float_as_uint(v));
        }
        __threadfence();
        bar_sync(1, NCOMP);
        if (t == 0) {
            st_rlx32(reinterpret_cast<uint32_t*>(&g_qflag[h * 2]) + s, 1u);
            wait_flags(&g_qflag[h * 2]);
        }
        bar_sync(1, NCOMP);
        if (t < DH) {
            const float* qp = &g_qpart[(h * 4) * DH + t];
            const float v0 = ld_rlx32f(qp), v1 = ld_rlx32f(qp + DH), v2 = ld_rlx32f(qp + 2 * DH), v3 = ld_rlx32f(qp + 3 * DH);
            sm.q[t] = rbf((v0 + v1) + (v2 + v3));
        }
        bar_sync(1, NCOMP);
    }
    TS(1);

    uint32_t wor[32];
    uint32_t gur[32];
    uint32_t wdr[16];
    const bool ffn = cta < NFFN;
    auto load_wo = [&]() {
        const __nv_bfloat16* b = wo + (size_t)(cta * 32) * DM + 2 * t;
#pragma unroll
        for (int r = 0; r < 32; r++) wor[r] = ldg32(b + r * DM);
    };
    auto load_ffn = [&]() {
        if (ffn) {
            const int cp = lane & 15;
            const __nv_bfloat16* b = (cp < 8 ? wg : wu) + (size_t)(64 * w + 32 * (lane >> 4)) * DF + cta * 16 + 2 * (cp & 7);
#pragma unroll
            for (int j = 0; j < 32; j++) gur[j] = ldg32_pf256(b + (size_t)j * DF);
            const __nv_bfloat16* d = wd + (size_t)(cta * 16) * DM + 2 * t;
#pragma unroll
            for (int f = 0; f < 16; f++) wdr[f] = ldg32(d + f * DM);
        } else {
#pragma unroll
            for (int j = 0; j < 32; j++) gur[j] = 0;
#pragma unroll
            for (int f = 0; f < 16; f++) wdr[f] = 0;
        }
    };
    float wof[64];
    auto unpack_wo = [&]() {
#pragma unroll
        for (int r = 0; r < 32; r++) { wof[2 * r] = bf_lo(wor[r]); wof[2 * r + 1] = bf_hi(wor[r]); }
    };

    if (w < 8) {
        {
            float qr[8];
            const float4 qa = *reinterpret_cast<const float4*>(&sm.q[(lane & 15) * 8]);
            const float4 qb = *reinterpret_cast<const float4*>(&sm.q[(lane & 15) * 8 + 4]);
            qr[0] = qa.x; qr[1] = qa.y; qr[2] = qa.z; qr[3] = qa.w; qr[4] = qb.x; qr[5] = qb.y; qr[6] = qb.z; qr[7] = qb.w;
#pragma unroll 1
            for (int i = 0; i < NKT; i++) {
                const int sl = i % NSLOT;
                mbar_wait(s2u(&sm.full[sl]), (i / NSLOT) & 1);
                const uint4* tp = reinterpret_cast<const uint4*>(sm.ring[sl]) + w * 128 + lane;
                uint4 kv[4];
#pragma unroll
                for (int j = 0; j < 4; j++) kv[j] = tp[j * 32];
                float d[4];
#pragma unroll
                for (int j = 0; j < 4; j++) {
                    float a = qr[0] * bf_lo(kv[j].x), b = qr[1] * bf_hi(kv[j].x);
                    a = fmaf(qr[2], bf_lo(kv[j].y), a); b = fmaf(qr[3], bf_hi(kv[j].y), b);
                    a = fmaf(qr[4], bf_lo(kv[j].z), a); b = fmaf(qr[5], bf_hi(kv[j].z), b);
                    a = fmaf(qr[6], bf_lo(kv[j].w), a); b = fmaf(qr[7], bf_hi(kv[j].w), b);
                    d[j] = a + b;
                }
                __syncwarp();
                if (lane == 0) mbar_arrive(s2u(&sm.empty[sl]));
                const bool b3 = lane & 8, b2 = lane & 4;
                float e0 = (b3 ? d[2] : d[0]) + __shfl_xor_sync(0xffffffffu, b3 ? d[0] : d[2], 8);
                float e1 = (b3 ? d[3] : d[1]) + __shfl_xor_sync(0xffffffffu, b3 ? d[1] : d[3], 8);
                float f = (b2 ? e1 : e0) + __shfl_xor_sync(0xffffffffu, b2 ? e0 : e1, 4);
                f += __shfl_xor_sync(0xffffffffu, f, 2);
                f += __shfl_xor_sync(0xffffffffu, f, 1);
                if ((lane & 3) == 0) {
                    const int j = ((lane >> 3) & 1) * 2 + ((lane >> 2) & 1);
                    const int key = i * 64 + w * 8 + j * 2 + (lane >> 4);
                    const float sv = rbf(f) * 0.08838834764831845f;
                    sm.sc[key] = __bfloat16_as_ushort(__float2bfloat16_rn(sv));
                }
            }
        }
        TS(2);
        bar_sync(2, 256);
        if (t < 128) {
            st_rlx128(&g_scores[cta * 128 + t], reinterpret_cast<const uint4*>(sm.sc)[t]);
            __threadfence();
        }
        bar_sync(2, 256);
        if (t == 0) {
            st_rlx32(reinterpret_cast<uint32_t*>(&g_sflag[h * 2]) + s, 1u);
            wait_flags(&g_sflag[h * 2]);
        }
        bar_sync(2, 256);
        TS(3);
        {
            const uint4 u0 = ld_rlx128(&g_scores[h * 512 + t]);
            const uint4 u1 = ld_rlx128(&g_scores[h * 512 + 256 + t]);
            float e[16];
            e[0] = bf_lo(u0.x); e[1] = bf_hi(u0.x); e[2] = bf_lo(u0.y); e[3] = bf_hi(u0.y);
            e[4] = bf_lo(u0.z); e[5] = bf_hi(u0.z); e[6] = bf_lo(u0.w); e[7] = bf_hi(u0.w);
            e[8] = bf_lo(u1.x); e[9] = bf_hi(u1.x); e[10] = bf_lo(u1.y); e[11] = bf_hi(u1.y);
            e[12] = bf_lo(u1.z); e[13] = bf_hi(u1.z); e[14] = bf_lo(u1.w); e[15] = bf_hi(u1.w);
            float m = e[0];
#pragma unroll
            for (int j = 1; j < 16; j++) m = fmaxf(m, e[j]);
#pragma unroll
            for (int o = 16; o > 0; o >>= 1) m = fmaxf(m, __shfl_xor_sync(0xffffffffu, m, o));
            if (lane == 0) sm.stat[w] = m;
            bar_sync(2, 256);
#pragma unroll
            for (int j = 0; j < 8; j++) m = fmaxf(m, sm.stat[j]);
            float sum = 0.f;
#pragma unroll
            for (int j = 0; j < 16; j++) { e[j] = __expf(e[j] - m); sum += e[j]; }
#pragma unroll
            for (int o = 16; o > 0; o >>= 1) sum += __shfl_xor_sync(0xffffffffu, sum, o);
            if (lane == 0) sm.stat[16 + w] = sum;
            bar_sync(2, 256);
            sum = 0.f;
#pragma unroll
            for (int j = 0; j < 8; j++) sum += sm.stat[16 + j];
            const float inv = __fdiv_rn(1.0f, sum);
            float* pp = sm.p + (t >> 2) * 32 + (t & 3);
#pragma unroll
            for (int j = 0; j < 8; j++) {
                pp[j * 4] = rbf(e[j] * inv);
                pp[2048 + j * 4] = rbf(e[8 + j] * inv);
            }
            bar_sync(2, 256);
        }
        TS(4);
        float acc[8];
#pragma unroll
        for (int j = 0; j < 8; j++) acc[j] = 0.f;
        auto vtile = [&](int jt) {
            const int i = NKT + jt;
            const int sl = i % NSLOT;
            const float4 pv = *reinterpret_cast<const float4*>(&sm.p[jt * 256 + w * 32 + (lane >> 2) * 4]);
            mbar_wait(s2u(&sm.full[sl]), (i / NSLOT) & 1);
            const uint4* tp = reinterpret_cast<const uint4*>(sm.ring[sl]) + w * 128 + lane;
            uint4 vv[4];
#pragma unroll
            for (int j = 0; j < 4; j++) vv[j] = tp[j * 32];
            const float pj[4] = {pv.x, pv.y, pv.z, pv.w};
#pragma unroll
            for (int j = 0; j < 4; j++) {
                acc[0] = fmaf(pj[j], bf_lo(vv[j].x), acc[0]); acc[1] = fmaf(pj[j], bf_hi(vv[j].x), acc[1]);
                acc[2] = fmaf(pj[j], bf_lo(vv[j].y), acc[2]); acc[3] = fmaf(pj[j], bf_hi(vv[j].y), acc[3]);
                acc[4] = fmaf(pj[j], bf_lo(vv[j].z), acc[4]); acc[5] = fmaf(pj[j], bf_hi(vv[j].z), acc[5]);
                acc[6] = fmaf(pj[j], bf_lo(vv[j].w), acc[6]); acc[7] = fmaf(pj[j], bf_hi(vv[j].w), acc[7]);
            }
            if (i + NSLOT < NKT + NVT) {
                __syncwarp();
                if (lane == 0) mbar_arrive(s2u(&sm.empty[sl]));
            }
        };
#pragma unroll 1
        for (int jt = 0; jt <= JW; jt++) vtile(jt);
        load_wo();
#pragma unroll 1
        for (int jt = JW + 1; jt <= JG; jt++) vtile(jt);
        load_ffn();
#pragma unroll 1
        for (int jt = JG + 1; jt < NVT - 1; jt++) vtile(jt);
        unpack_wo();
        TS(5);
        vtile(NVT - 1);
        TS(6);
        {
            const bool b4 = lane & 16, b3 = lane & 8, b2 = lane & 4;
            float r4[4], r2[2];
#pragma unroll
            for (int j = 0; j < 4; j++) r4[j] = (b4 ? acc[4 + j] : acc[j]) + __shfl_xor_sync(0xffffffffu, b4 ? acc[j] : acc[4 + j], 16);
#pragma unroll
            for (int j = 0; j < 2; j++) r2[j] = (b3 ? r4[2 + j] : r4[j]) + __shfl_xor_sync(0xffffffffu, b3 ? r4[j] : r4[2 + j], 8);
            const float r1 = (b2 ? r2[1] : r2[0]) + __shfl_xor_sync(0xffffffffu, b2 ? r2[0] : r2[1], 4);
            const int dim = (lane & 3) * 8 + (b4 ? 4 : 0) + (b3 ? 2 : 0) + (b2 ? 1 : 0);
            sm.part[w][dim] = r1;
        }
    } else {
        mbar_wait(s2u(&sm.full[(NKT + JW) % NSLOT]), ((NKT + JW) / NSLOT) & 1);
        load_wo();
        mbar_wait(s2u(&sm.full[(NKT + JG) % NSLOT]), ((NKT + JG) / NSLOT) & 1);
        load_ffn();
        unpack_wo();
    }
    bar_sync(1, NCOMP);

    float y0, y1;
    {
        float v = 0.f;
#pragma unroll
        for (int i = 0; i < 8; i++) v += sm.part[i][lane];
        sm.wloc[w][lane] = rbf(v);
        __syncwarp();
        float ya = 0.f, yb = 0.f, yc = 0.f, yd = 0.f;
#pragma unroll
        for (int i = 0; i < 8; i++) {
            const float4 o4 = *reinterpret_cast<const float4*>(&sm.wloc[w][4 * i]);
            ya = fmaf(o4.x, wof[8 * i + 0], ya); yb = fmaf(o4.x, wof[8 * i + 1], yb);
            yc = fmaf(o4.y, wof[8 * i + 2], yc); yd = fmaf(o4.y, wof[8 * i + 3], yd);
            ya = fmaf(o4.z, wof[8 * i + 4], ya); yb = fmaf(o4.z, wof[8 * i + 5], yb);
            yc = fmaf(o4.w, wof[8 * i + 6], yc); yd = fmaf(o4.w, wof[8 * i + 7], yd);
        }
        y0 = ya + yc; y1 = yb + yd;
    }
    red_v4(&g_acc1[slot_off], y0, y1, 1.0f, 0.0f);
    TS(7);
    if (!ffn) return;

    float guf[64], wdf[32];
#pragma unroll
    for (int j = 0; j < 32; j++) { guf[2 * j] = bf_lo(gur[j]); guf[2 * j + 1] = bf_hi(gur[j]); }
#pragma unroll
    for (int f = 0; f < 16; f++) { wdf[2 * f] = bf_lo(wdr[f]); wdf[2 * f + 1] = bf_hi(wdr[f]); }

    float h0, h1;
    {
        const uint32_t want = __float_as_uint((float)NCTA);
        uint4 v;
        int n = 0;
        if (lane == (cta & 31)) {
            do { v = ld_rlx128(&g_acc1[slot_off]); if (++n > SPIN_LIMIT) __trap(); } while (v.z != want);
        }
        __syncwarp();
        do { v = ld_rlx128(&g_acc1[slot_off]); if (++n > SPIN_LIMIT) __trap(); } while (v.z != want);
        h0 = rbf(x0 + rbf(__uint_as_float(v.x)));
        h1 = rbf(x1 + rbf(__uint_as_float(v.y)));
    }
    TS(8);
    if (cta == 0 && t < 2 * HQ) {
        st_rlx128(&g_qflag[t], make_uint4(0, 0, 0, 0));
        st_rlx128(&g_sflag[t], make_uint4(0, 0, 0, 0));
    }
    float z0, z1;
    {
        float n0, n1;
        layernorm2(h0, h1, sm.stat, w, lane, n0, n1);
        *reinterpret_cast<float2*>(&sm.wloc[w][2 * lane + (lane >= 16 ? 4 : 0)]) = make_float2(n0, n1);
        __syncwarp();
        float ga = 0.f, gb = 0.f, gc = 0.f, gd = 0.f;
        const float* hp = &sm.wloc[w][(lane >> 4) * 36];
#pragma unroll
        for (int i = 0; i < 8; i++) {
            const float4 o4 = *reinterpret_cast<const float4*>(hp + 4 * i);
            ga = fmaf(o4.x, guf[8 * i + 0], ga); gb = fmaf(o4.x, guf[8 * i + 1], gb);
            gc = fmaf(o4.y, guf[8 * i + 2], gc); gd = fmaf(o4.y, guf[8 * i + 3], gd);
            ga = fmaf(o4.z, guf[8 * i + 4], ga); gb = fmaf(o4.z, guf[8 * i + 5], gb);
            gc = fmaf(o4.w, guf[8 * i + 6], gc); gd = fmaf(o4.w, guf[8 * i + 7], gd);
        }
        const float c0 = ga + gc, c1 = gb + gd;
        const bool hi = lane & 16;
        const float cs = (hi ? c1 : c0) + __shfl_xor_sync(0xffffffffu, hi ? c0 : c1, 16);
        sm.part[w][lane] = cs;
        bar_sync(1, NCOMP);
        float v = 0.f;
#pragma unroll
        for (int i = 0; i < 10; i++) v += sm.part[i][lane];
        v = rbf(v);
        const float u = __shfl_xor_sync(0xffffffffu, v, 8);
        const float inner = 0.7978845608028654f * (v + 0.044715f * v * v * v);
        const float gl = rbf(0.5f * v * (1.0f + tanhf(inner)));
        const float act = rbf(gl * u);
        if ((lane & 8) == 0) sm.wloc[w][2 * (lane & 7) + (lane >> 4)] = act;
        __syncwarp();
        float za = 0.f, zb = 0.f, zc = 0.f, zd = 0.f;
#pragma unroll
        for (int i = 0; i < 4; i++) {
            const float4 o4 = *reinterpret_cast<const float4*>(&sm.wloc[w][4 * i]);
            za = fmaf(o4.x, wdf[8 * i + 0], za); zb = fmaf(o4.x, wdf[8 * i + 1], zb);
            zc = fmaf(o4.y, wdf[8 * i + 2], zc); zd = fmaf(o4.y, wdf[8 * i + 3], zd);
            za = fmaf(o4.z, wdf[8 * i + 4], za); zb = fmaf(o4.z, wdf[8 * i + 5], zb);
            zc = fmaf(o4.w, wdf[8 * i + 6], zc); zd = fmaf(o4.w, wdf[8 * i + 7], zd);
        }
        z0 = za + zc; z1 = zb + zd;
    }
    TS(9);
    const float4 old = atom_v4(&g_acc2[slot_off], z0, z1, 1.0f, 0.0f);
    if (old.z == (float)(NFFN - 1)) {
        const float r0 = h0 + rbf(old.x + z0), r1 = h1 + rbf(old.y + z1);
        *reinterpret_cast<__nv_bfloat162*>(out + 2 * t) = __floats2bfloat162_rn(r0, r1);
        st_rlx128(&g_acc1[slot_off], make_uint4(0, 0, 0, 0));
    }
    TS(10);
}

typedef CUresult (*EncodeTiledFn)(CUtensorMap*, CUtensorMapDataType, cuuint32_t, void*, const cuuint64_t*, const cuuint64_t*,
                                  const cuuint32_t*, const cuuint32_t*, CUtensorMapInterleave, CUtensorMapSwizzle,
                                  CUtensorMapL2promotion, CUtensorMapFloatOOBfill);

}

extern "C" void kernel_launch(void* const* d_in, const int* in_sizes, int n_in, void* d_out, int out_size) {
    (void)in_sizes; (void)n_in; (void)out_size;
    static bool ready = false;
    static CUtensorMap vmap;
    static void* vptr = nullptr;
    if (!ready || vptr != d_in[2]) {
        EncodeTiledFn enc = nullptr;
        cudaDriverEntryPointQueryResult qr;
        cudaGetDriverEntryPoint("cuTensorMapEncodeTiled", (void**)&enc, cudaEnableDefault, &qr);
        const cuuint64_t gdim[2] = {(cuuint64_t)DH, (cuuint64_t)HQ * SK};
        const cuuint64_t gstr[1] = {(cuuint64_t)DH * 2};
        const cuuint32_t box[2] = {32, 256};
        const cuuint32_t estr[2] = {1, 1};
        enc(&vmap, CU_TENSOR_MAP_DATA_TYPE_BFLOAT16, 2, d_in[2], gdim, gstr, box, estr, CU_TENSOR_MAP_INTERLEAVE_NONE,
            CU_TENSOR_MAP_SWIZZLE_NONE, CU_TENSOR_MAP_L2_PROMOTION_L2_256B, CU_TENSOR_MAP_FLOAT_OOB_FILL_NONE);
        cudaFuncSetAttribute(fused_block_kernel, cudaFuncAttributeMaxDynamicSharedMemorySize, (int)sizeof(Smem));
        vptr = d_in[2];
        ready = true;
    }
    fused_block_kernel<<<NCTA, NTHREADS, sizeof(Smem), cudaStreamPerThread>>>(
        (const __nv_bfloat16*)d_in[0], (const __nv_bfloat16*)d_in[1], vmap, (const __nv_bfloat16*)d_in[3],
        (const __nv_bfloat16*)d_in[4], (const __nv_bfloat16*)d_in[6], (const __nv_bfloat16*)d_in[7],
        (const __nv_bfloat16*)d_in[8], (__nv_bfloat16*)d_out);
}
```

```cpp
#include <cuda_runtime.h>
#include <cuda_bf16.h>
#include <cuda.h>
#include <stdint.h>

namespace {

constexpr int DM = 640, HQ = 32, DH = 128, SK = 4096, DF = 1728;
constexpr int NCTA = 128;
constexpr int NFFN = DF / 16;
constexpr int NCOMP = 320;
constexpr int NTHREADS = 352;
constexpr int TILE = 16384;
constexpr int NSLOT = 13;
constexpr int SPIN_LIMIT = 1 << 22;

#define NK0 4
#define CAP 8
#define FSER 3
#define FD 15
#define FU 14
#define FG 12

enum { B_WQ = 0, B_QX = 2, B_K = 3, B_WO = 19, B_V = 20, B_G = 36, B_U, B_D, B_FREADY,
       B_OX = 40,
       B_EWQ = 41, B_EK = 43, B_EWO = 59, B_EV = 60, NBAR = 67 };

struct __align__(1024) Smem {
    uint8_t  ring[NSLOT * TILE];
    float    sc[1024];
    uint32_t p[512];
    uint16_t xn[DM];
    float2   part[10][34];
    float    ox[2][64];
    float    stat[32];
    float    wred[16];
    uint32_t q[DH / 2];
    float2   qp[64];
    float    fscale;
    uint64_t bar[NBAR];
    unsigned long long pts[40];
};

__device__ __align__(256) uint4    g_ml[NCTA * 2];
__device__ __align__(256) uint4    g_epoch;
__device__ __align__(256) float4   g_acc1[160 * 16];
__device__ __align__(256) float4   g_acc2[160 * 16];
#define TS_DECL
#define TSP(i)
#define TSX(i)
#define PTS(i)
#define TS(i)
#define TS_FLUSH

#define CK_DECL
#define CK(i)
#define CK_FLUSH

__device__ __forceinline__ uint32_t s2u(const void* p) { return (uint32_t)__cvta_generic_to_shared(p); }
__device__ __forceinline__ void mbar_init(uint32_t bar, uint32_t cnt) {
    asm volatile("mbarrier.init.shared::cta.b64 [%0], %1;" ::"r"(bar), "r"(cnt) : "memory");
}
__device__ __forceinline__ void mbar_expect(uint32_t bar, uint32_t bytes) {
    asm volatile("mbarrier.arrive.expect_tx.shared::cta.b64 _, [%0], %1;" ::"r"(bar), "r"(bytes) : "memory");
}
__device__ __forceinline__ void mbar_arrive(uint32_t bar) {
    asm volatile("mbarrier.arrive.shared::cta.b64 _, [%0];" ::"r"(bar) : "memory");
}
__device__ __forceinline__ void mbar_wait(uint32_t bar) {
    asm volatile("{\n .reg .pred p;\n .reg .u32 n;\n mov.u32 n, 0;\n"
                 "W: mbarrier.try_wait.parity.shared::cta.b64 p, [%0], 0;\n @p bra D;\n"
                 " add.u32 n, n, 1;\n setp.lt.u32 p, n, %1;\n @p bra W;\n trap;\n"
                 "D:\n}" ::"r"(bar), "n"(SPIN_LIMIT) : "memory");
}
__device__ __forceinline__ void mbar_wait_cluster(uint32_t bar) {
    asm volatile("{\n .reg .pred p;\n .reg .u32 n;\n mov.u32 n, 0;\n"
                 "W: mbarrier.try_wait.parity.acquire.cluster.shared::cta.b64 p, [%0], 0;\n @p bra D;\n"
                 " add.u32 n, n, 1;\n setp.lt.u32 p, n, %1;\n @p bra W;\n trap;\n"
                 "D:\n}" ::"r"(bar), "n"(SPIN_LIMIT) : "memory");
}
__device__ __forceinline__ bool mbar_test(uint32_t bar) {
    uint32_t ok;
    asm volatile("{\n .reg .pred p;\n mbarrier.test_wait.parity.shared::cta.b64 p, [%1], 0;\n selp.u32 %0, 1, 0, p;\n}"
                 : "=r"(ok) : "r"(bar) : "memory");
    return ok;
}
__device__ __forceinline__ void bulk_load(uint32_t dst, const void* src, uint32_t bytes, uint32_t bar) {
    asm volatile("cp.async.bulk.shared::cluster.global.mbarrier::complete_tx::bytes [%0], [%1], %2, [%3];"
                 ::"r"(dst), "l"(src), "r"(bytes), "r"(bar) : "memory");
}
__device__ __forceinline__ void tma_3d(uint32_t dst, const CUtensorMap* m, int c0, int c1, int c2, uint32_t bar) {
    asm volatile("cp.async.bulk.tensor.3d.shared::cluster.global.mbarrier::complete_tx::bytes [%0], [%1, {%3, %4, %5}], [%2];"
                 ::"r"(dst), "l"(m), "r"(bar), "r"(c0), "r"(c1), "r"(c2) : "memory");
}
__device__ __forceinline__ uint32_t mapa(uint32_t addr, uint32_t rank) {
    uint32_t r;
    asm volatile("mapa.shared::cluster.u32 %0, %1, %2;" : "=r"(r) : "r"(addr), "r"(rank));
    return r;
}
__device__ __forceinline__ void bar_sync(int id, int n) { asm volatile("bar.sync %0, %1;" ::"r"(id), "r"(n) : "memory"); }
__device__ __forceinline__ void mma_bf16(float (&c)[4], uint32_t a0, uint32_t a1, uint32_t a2, uint32_t a3, uint32_t b0, uint32_t b1) {
    asm volatile("mma.sync.aligned.m16n8k16.row.col.f32.bf16.bf16.f32 {%0,%1,%2,%3}, {%4,%5,%6,%7}, {%8,%9}, {%0,%1,%2,%3};"
                 : "+f"(c[0]), "+f"(c[1]), "+f"(c[2]), "+f"(c[3]) : "r"(a0), "r"(a1), "r"(a2), "r"(a3), "r"(b0), "r"(b1));
}
__device__ __forceinline__ void mma_bf16(float (&c)[4], const uint4& a, uint32_t b0, uint32_t b1) { mma_bf16(c, a.x, a.y, a.z, a.w, b0, b1); }
__device__ __forceinline__ uint4 ldsm_t(uint32_t addr) {
    uint4 r;
    asm volatile("ldmatrix.sync.aligned.m8n8.x4.trans.shared.b16 {%0,%1,%2,%3}, [%4];"
                 : "=r"(r.x), "=r"(r.y), "=r"(r.z), "=r"(r.w) : "r"(addr) : "memory");
    return r;
}
__device__ __forceinline__ uint4 ld_rlx128(const void* p) {
    uint4 v;
    asm volatile("ld.relaxed.gpu.global.v4.u32 {%0,%1,%2,%3}, [%4];" : "=r"(v.x), "=r"(v.y), "=r"(v.z), "=r"(v.w) : "l"(p) : "memory");
    return v;
}
__device__ __forceinline__ void st_tagged(void* p, uint32_t a, uint32_t b, uint32_t tag) {
    const uint64_t lo = ((uint64_t)tag << 32) | a, hi = ((uint64_t)tag << 32) | b;
    asm volatile("st.relaxed.gpu.global.v2.b64 [%0], {%1,%2};" ::"l"(p), "l"(lo), "l"(hi) : "memory");
}
__device__ __forceinline__ bool ld_tagged(const void* p, uint32_t tag, uint32_t& a, uint32_t& b) {
    uint64_t lo, hi;
    asm volatile("ld.relaxed.gpu.global.v2.b64 {%0,%1}, [%2];" : "=l"(lo), "=l"(hi) : "l"(p) : "memory");
    a = (uint32_t)lo; b = (uint32_t)hi;
    return (uint32_t)(lo >> 32) == tag && (uint32_t)(hi >> 32) == tag;
}
template <int N, int S0, int S1>
__device__ __forceinline__ void poll(const uint4* p, uint32_t tag, uint32_t (&a)[N], uint32_t (&b)[N]) {
    int n = 0;
#pragma unroll 1
    while (true) {
        bool ok = true;
#pragma unroll
        for (int i = 0; i < N; i++) ok &= ld_tagged(p + (i & 3) * S0 + (i >> 2) * S1, tag, a[i], b[i]);
        if (ok) break;
        if (++n > SPIN_LIMIT) __trap();
        __nanosleep(64);
    }
}
__device__ __forceinline__ void st_rlx128(void* p, uint4 v) {
    asm volatile("st.relaxed.gpu.global.v4.u32 [%0], {%1,%2,%3,%4};" ::"l"(p), "r"(v.x), "r"(v.y), "r"(v.z), "r"(v.w) : "memory");
}
__device__ __forceinline__ void st_rlx32(void* p, uint32_t v) {
    asm volatile("st.relaxed.gpu.global.u32 [%0], %1;" ::"l"(p), "r"(v) : "memory");
}
__device__ __forceinline__ void red_v4(void* p, float a, float b, float c, float d) {
    asm volatile("red.relaxed.gpu.global.add.v4.f32 [%0], {%1,%2,%3,%4};" ::"l"(p), "f"(a), "f"(b), "f"(c), "f"(d) : "memory");
}
__device__ __forceinline__ float4 atom_v4(void* p, float a, float b, float c, float d) {
    float4 r;
    asm volatile("atom.relaxed.gpu.global.add.v4.f32 {%0,%1,%2,%3}, [%4], {%5,%6,%7,%8};"
                 : "=f"(r.x), "=f"(r.y), "=f"(r.z), "=f"(r.w) : "l"(p), "f"(a), "f"(b), "f"(c), "f"(d) : "memory");
    return r;
}
__device__ __forceinline__ float bf_lo(uint32_t v) { return __uint_as_float(v << 16); }
__device__ __forceinline__ float bf_hi(uint32_t v) { return __uint_as_float(v & 0xffff0000u); }
__device__ __forceinline__ uint16_t bf_bits(float v) { return __bfloat16_as_ushort(__float2bfloat16_rn(v)); }
__device__ __forceinline__ uint32_t bf_pack(float lo, float hi) {
    const __nv_bfloat162 v = __floats2bfloat162_rn(lo, hi);
    return *reinterpret_cast<const uint32_t*>(&v);
}
__device__ __forceinline__ float sel4(int t, float a, float b, float c, float d) { return (t & 2) ? ((t & 1) ? d : c) : ((t & 1) ? b : a); }
__device__ __forceinline__ float rbf(float v) { return __bfloat162float(__float2bfloat16_rn(v)); }
__device__ __forceinline__ float expdiff(float a, float b) {
    float r;
    asm("ex2.approx.ftz.f32 %0, %1;" : "=f"(r) : "f"((a - b) * 1.4426950408889634f));
    return r;
}
__device__ __forceinline__ float shx(float v, int m) { return __shfl_xor_sync(0xffffffffu, v, m); }

__device__ __forceinline__ float2 layernorm2(float a0, float a1, float* stat, int w, int lane) {
    const float piv = __shfl_sync(0xffffffffu, a0, 0);
    const float d0 = a0 - piv, d1 = a1 - piv;
    float s1 = d0 + d1, s2 = d0 * d0 + d1 * d1;
#pragma unroll
    for (int o = 16; o > 0; o >>= 1) { s1 += shx(s1, o); s2 += shx(s2, o); }
    if (lane == 0) {
        const float mu = s1 * (1.0f / 64.0f);
        *reinterpret_cast<float2*>(stat + 2 * w) = make_float2(piv + mu, fmaxf(s2 - s1 * mu, 0.0f));
    }
    bar_sync(1, NCOMP);
    float mw[10], ms = 0.f, m2 = 0.f;
#pragma unroll
    for (int i = 0; i < 5; i++) {
        const float4 v = *reinterpret_cast<const float4*>(stat + 4 * i);
        mw[2 * i] = v.x; mw[2 * i + 1] = v.z;
        ms += v.x + v.z; m2 += v.y + v.w;
    }
    const float mean = ms * 0.1f;
    float dv = 0.f;
#pragma unroll
    for (int i = 0; i < 10; i++) { const float d = mw[i] - mean; dv = fmaf(d, d, dv); }
    const float var = (m2 + 64.0f * dv) * (1.0f / 640.0f);
    const float mb = rbf(mean);
    float sq;
    asm("sqrt.approx.f32 %0, %1;" : "=f"(sq) : "f"(rbf(rbf(var) + 1e-5f)));
    const float den = rbf(sq);
    return make_float2(__fdividef(rbf(a0 - mb), den), __fdividef(rbf(a1 - mb), den));
}

__global__ void __cluster_dims__(2, 1, 1) __launch_bounds__(NTHREADS, 1)
fused_block_kernel(const __nv_bfloat16* __restrict__ x, const __nv_bfloat16* __restrict__ kc, __nv_bfloat16* __restrict__ out,
                   const __grid_constant__ CUtensorMap qmap, const __grid_constant__ CUtensorMap omap,
                   const __grid_constant__ CUtensorMap vmap, const __grid_constant__ CUtensorMap gmap,
                   const __grid_constant__ CUtensorMap umap, const __grid_constant__ CUtensorMap dmap) {
    extern __shared__ __align__(1024) uint8_t smem_raw[];
    Smem& sm = *reinterpret_cast<Smem*>(smem_raw);
    const int t = threadIdx.x, w = t >> 5, lane = t & 31;
    const int cta = blockIdx.x, h = cta >> 2, s = cta & 3;
    const bool ffn = cta < NFFN;
    const uint32_t bar0 = s2u(sm.bar), ring0 = s2u(sm.ring);
#define BAR(i) (bar0 + 8 * (i))

    if (w == 10) {
        PTS(0);
        const uint8_t* kp = reinterpret_cast<const uint8_t*>(kc) + (size_t)cta * (16 * TILE);
        if (lane == 0) {
#pragma unroll
            for (int i = 0; i < B_K + 8; i++) mbar_init(BAR(i), 1);
            asm volatile("fence.mbarrier_init.release.cluster;" ::: "memory");
            mbar_expect(BAR(B_WQ), 40960);
            tma_3d(ring0, &qmap, 0, (s & 1) * 320 + (s >> 1) * 160, 2 * h, BAR(B_WQ));
#pragma unroll 1
            for (int i = 0; i < NK0; i++) {
                if (i == 2) {
                    mbar_expect(BAR(B_WQ + 1), 40960);
                    tma_3d(ring0 + 40960, &qmap, 0, (s & 1) * 320 + 160 - (s >> 1) * 160, 2 * h, BAR(B_WQ + 1));
                }
                mbar_expect(BAR(B_K + i), TILE);
                bulk_load(ring0 + (5 + i) * TILE, kp + (size_t)i * TILE, TILE, BAR(B_K + i));
            }
            mbar_expect(BAR(B_QX), 512);
#pragma unroll
            for (int i = B_K + 8; i < NBAR; i++)
                mbar_init(BAR(i), i < B_OX ? 1 : i == B_OX ? 5 : i < B_EK ? 8 : i < B_EWO ? 4 : i == B_EWO ? 10 : 8);
            asm volatile("fence.mbarrier_init.release.cluster;" ::: "memory");
            mbar_expect(BAR(B_OX), 256);
        }
        bar_sync(0, NTHREADS);
        asm volatile("barrier.cluster.arrive.relaxed.aligned;" ::: "memory");
        asm volatile("barrier.cluster.wait.aligned;" ::: "memory");
        if (lane == 0) {
            PTS(1);
#pragma unroll 1
            for (int n = NK0; n < 37; n++) {
                if (n < CAP) mbar_wait(BAR(B_WQ + (n >= NK0 + 2)));
                else mbar_wait(BAR(B_K + (n - CAP < 16 ? n - CAP : n - CAP < 21 ? 16 : n - CAP - 4)));
                if (n >= 8) mbar_wait(n < 10 ? BAR(B_EWQ) : n < 13 ? BAR(B_EWQ + 1) : n < 29 ? BAR(B_EK + n - 13) : n < 34 ? BAR(B_EWO) : BAR(B_EV + n - 34));
                const uint32_t dst = ring0 + ((5 + n) % NSLOT) * TILE;
                if (n < 16) {
                    mbar_expect(BAR(B_K + n), TILE);
                    bulk_load(dst, kp + (size_t)n * TILE, TILE, BAR(B_K + n));
                } else if (n == 18 || n == 20) {
                    if (n == 18) mbar_expect(BAR(B_WO), 81920);
                    tma_3d(ring0 + 8 * TILE + (n - 18) * 20480, &omap, 0, h * 128 + (s & 1) * 64, (n - 18) / 2 * 5, BAR(B_WO));
                } else if (n > 20) {
                    mbar_expect(BAR(B_V + n - 21), TILE);
                    tma_3d(dst, &vmap, 0, cta * 1024 + (n - 21) * 64, 0, BAR(B_V + n - 21));
                }
            }
            PTS(2);
            if (ffn) {
                mbar_wait(BAR(B_EV + 6));
                mbar_wait(BAR(B_V + FG));
                mbar_expect(BAR(B_G), 20480);
                tma_3d(ring0 + 3 * TILE, &gmap, cta * 16, 0, 0, BAR(B_G));
                if (FSER & 1) mbar_wait(BAR(B_G));
                mbar_wait(BAR(B_V + FU));
                mbar_expect(BAR(B_U), 20480);
                tma_3d(ring0 + 3 * TILE + 20480, &umap, cta * 16, 0, 0, BAR(B_U));
                if (FSER & 2) mbar_wait(BAR(B_U));
                mbar_wait(BAR(B_V + FD));
                mbar_expect(BAR(B_D), 20480);
                tma_3d(ring0 + 3 * TILE + 40960, &dmap, 0, cta * 16, 0, BAR(B_D));
            }
        }
        return;
    }

    TS_DECL
    CK_DECL
    TS(0);
    const int g = lane >> 2, tq = lane & 3;
    const int col = 64 * w + 16 * tq + g;
    uint32_t tag;
    asm volatile("ld.relaxed.gpu.global.u32 %0, [%1];" : "=r"(tag) : "l"(&g_epoch) : "memory");
    uint16_t xa, xb;
    asm volatile("ld.global.nc.u16 %0, [%1];" : "=h"(xa) : "l"(x + col));
    asm volatile("ld.global.nc.u16 %0, [%1];" : "=h"(xb) : "l"(x + col + 8));
    if (w == 9 && lane < 5) {
        const CUtensorMap* m = lane == 0 ? &omap : lane == 1 ? &vmap : lane == 2 ? &gmap : lane == 3 ? &umap : &dmap;
        asm volatile("prefetch.tensormap [%0];" ::"l"(m) : "memory");
    }
    const size_t slot_off = (size_t)(t >> 1) * 16 + (t & 1);
    if (cta == NCTA - 1) st_rlx128(&g_acc2[slot_off], make_uint4(0, 0, 0, 0));
    bar_sync(0, NTHREADS);
    asm volatile("barrier.cluster.arrive.relaxed.aligned;" ::: "memory");
    tag += 1u;
    const int fpos = 64 * w + 16 * tq + (g >> 1) * 4 + (g & 1);
    const uint32_t lrow = (lane & 7) + ((lane >> 4) << 3), lchk = (lane >> 3) & 1;
    const float x0 = bf_lo(xa), x1 = bf_lo(xb);
    {
        const float2 xn = layernorm2(x0, x1, sm.stat, w, lane);
        sm.xn[fpos] = bf_bits(xn.x);
        sm.xn[fpos + 2] = bf_bits(xn.y);
        bar_sync(1, NCOMP);
        asm volatile("barrier.cluster.wait.aligned;" ::: "memory");
    }
    const uint32_t aoff = lrow * 128 + ((((w & 3) * 2 + lchk) ^ (lane & 7)) << 4);
    if (w < 8) {
        float c[4] = {0.f, 0.f, 0.f, 0.f};
#pragma unroll 1
        for (int hf = 0; hf < 2; hf++) {
            mbar_wait(BAR(B_WQ + hf));
            const uint16_t* xp = &sm.xn[(s & 1) * 320 + ((s >> 1) ^ hf) * 160 + tq * 4];
#pragma unroll 5
            for (int k = 0; k < 10; k++) {
                const uint4 a = ldsm_t(ring0 + hf * 40960 + (w >> 2) * 20480 + k * 2048 + aoff);
                const uint2 b = *reinterpret_cast<const uint2*>(xp + k * 16);
                mma_bf16(c, a, b.x, b.y);
            }
            if (lane == 0) mbar_arrive(BAR(B_EWQ + hf));
        }
        TS(11);
        if (tq == 0)
            asm volatile("st.async.weak.shared::cluster.mbarrier::complete_tx::bytes.v2.f32 [%0], {%1, %2}, [%3];"
                         ::"r"(mapa(s2u(&sm.qp[w * 8 + g]), (s & 1) ^ 1)), "f"(c[0]), "f"(c[2]), "r"(mapa(BAR(B_QX), (s & 1) ^ 1)) : "memory");
        mbar_wait_cluster(BAR(B_QX));
        if (tq == 0) {
            const float2 o = sm.qp[w * 8 + g];
            uint16_t* qh = reinterpret_cast<uint16_t*>(sm.q) + w * 16 + g;
            qh[0] = bf_bits(c[0] + o.x);
            qh[8] = bf_bits(c[2] + o.y);
        }
        bar_sync(3, 256);
        TS(1);
        float mx = -INFINITY;
        uint4 qf[4];
#pragma unroll
        for (int c = 0; c < 4; c++) qf[c] = *reinterpret_cast<const uint4*>(&sm.q[(c ^ (g & 1)) * 16 + tq * 4]);
#pragma unroll 1
        for (int i = w >> 2; i < 16; i += 2) {
            mbar_wait(BAR(B_K + i));
            const uint8_t* tp = sm.ring + ((5 + i) % NSLOT) * TILE + ((w & 3) * 16 + g) * 256 + tq * 16;
            uint4 ka[4], kb[4];
#pragma unroll
            for (int c = 0; c < 4; c++) {
                ka[c] = *reinterpret_cast<const uint4*>(tp + ((c ^ (g & 1)) * 64));
                kb[c] = *reinterpret_cast<const uint4*>(tp + 2048 + ((c ^ (g & 1)) * 64));
            }
            float c0[4] = {0.f, 0.f, 0.f, 0.f}, c1[4] = {0.f, 0.f, 0.f, 0.f};
#pragma unroll
            for (int c = 0; c < 4; c++) {
                mma_bf16(c0, ka[c].x, kb[c].x, ka[c].y, kb[c].y, qf[c].x, qf[c].y);
                mma_bf16(c1, ka[c].z, kb[c].z, ka[c].w, kb[c].w, qf[c].z, qf[c].w);
            }
            if (lane == 0) mbar_arrive(BAR(B_EK + i));
            const float slo = rbf(rbf((g & 1) ? c0[1] + c1[1] : c0[0] + c1[0]) * 0.08838834764831845f);
            const float shi = rbf(rbf((g & 1) ? c0[3] + c1[3] : c0[2] + c1[2]) * 0.08838834764831845f);
            mx = fmaxf(mx, fmaxf(slo, shi));
            if (tq < 2) sm.sc[i * 64 + (w & 3) * 16 + g + tq * 8] = tq ? shi : slo;
        }
        TS(2);
        mx = fmaxf(mx, shx(mx, 4)); mx = fmaxf(mx, shx(mx, 8)); mx = fmaxf(mx, shx(mx, 16));
        if (lane == 0) sm.wred[w] = mx;
        bar_sync(3, 256);
#pragma unroll
        for (int i = 0; i < 2; i++) {
            const float4 v = *reinterpret_cast<const float4*>(&sm.wred[4 * i]);
            mx = fmaxf(fmaxf(mx, fmaxf(v.x, v.y)), fmaxf(v.z, v.w));
        }
        const float4 sv = *reinterpret_cast<const float4*>(&sm.sc[4 * t]);
        const float e0 = expdiff(sv.x, mx), e1 = expdiff(sv.y, mx), e2 = expdiff(sv.z, mx), e3 = expdiff(sv.w, mx);
        uint32_t* pp = sm.p + (t >> 2) * 8 + (t & 1) * 4 + ((t >> 1) & 1);
        pp[0] = bf_pack(e0, e1);
        pp[2] = bf_pack(e2, e3);
        float sum = (e0 + e1) + (e2 + e3);
#pragma unroll
        for (int o = 16; o > 0; o >>= 1) sum += shx(sum, o);
        if (lane == 0) sm.wred[8 + w] = sum;
        bar_sync(2, 288);
    }
    float mc = 0.f;
    if (w == 8) {
        bar_sync(2, 288);
        float l = sm.wred[8 + (lane & 7)];
        mc = sm.wred[lane & 7];
        mc = fmaxf(mc, shx(mc, 1)); mc = fmaxf(mc, shx(mc, 2)); mc = fmaxf(mc, shx(mc, 4));
        l += shx(l, 1); l += shx(l, 2); l += shx(l, 4);
        if (lane < 2) st_tagged(&g_ml[cta * 2 + lane], __float_as_uint(mc), __float_as_uint(l), tag);
    }
    uint4 wof[16];
    mbar_wait(BAR(B_WO));
#pragma unroll
    for (int i = 0; i < 16; i++)
        wof[i] = ldsm_t(ring0 + 8 * TILE + w * 8192 + (i & 3) * 2048 + lrow * 128 + ((((i >> 2) * 2 + lchk) ^ (lane & 7)) << 4));
    if (lane == 0) mbar_arrive(BAR(B_EWO));
    if (w < 8) {
        float c0[4] = {0.f, 0.f, 0.f, 0.f}, c1[4] = {0.f, 0.f, 0.f, 0.f};
        float fs = 0.f;
        const bool mine = (w >> 2) == (s & 1);
        const uint32_t oa = s2u(&sm.ox[mine ? 0 : 1][(w & 3) * 16 + (g >> 1) * 4 + (g & 1) + tq * 2]);
        const uint32_t ra = mapa(oa, w >> 2), rb = mapa(BAR(B_OX), w >> 2);
#pragma unroll 1
        for (int v = 0; v < 16; v++) {
            uint2 b[4];
#pragma unroll
            for (int k = 0; k < 4; k++) b[k] = *reinterpret_cast<const uint2*>(&sm.p[v * 32 + k * 8 + tq * 2]);
            if (v == 15) {
                mbar_wait(BAR(B_FREADY));
                fs = sm.fscale;
                TS(5);
            }
            mbar_wait(BAR(B_V + v));
            CK(0);
            const uint32_t tp = ring0 + (v % NSLOT) * TILE + (w >> 2) * 8192 + aoff;
            uint4 a[4];
#pragma unroll
            for (int k = 0; k < 4; k++) a[k] = ldsm_t(tp + k * 2048);
            mma_bf16(c0, a[0], b[0].x, b[0].y); mma_bf16(c1, a[1], b[1].x, b[1].y);
            mma_bf16(c0, a[2], b[2].x, b[2].y); mma_bf16(c1, a[3], b[3].x, b[3].y);
            if (lane == 0 && v < 7) mbar_arrive(BAR(B_EV + v));
            if (v == 0) TS(3);
        }
        const float ov = (tq ? c0[2] + c1[2] : c0[0] + c1[0]) * fs;
        if (mine) {
            if (tq < 2) asm volatile("st.shared.f32 [%0], %1;" ::"r"(oa), "f"(ov) : "memory");
            __syncwarp();
            if (lane == 0) mbar_arrive(BAR(B_OX));
        } else if (tq < 2) {
            asm volatile("st.async.weak.shared::cluster.mbarrier::complete_tx::bytes.f32 [%0], %1, [%2];" ::"r"(ra), "f"(ov), "r"(rb) : "memory");
        }
        TS(6);
        CK(1);
    } else if (w == 8) {
        uint32_t a[1], b[1];
        mbar_wait(BAR(B_V + 3));
        poll<1, 0, 0>(&g_ml[(h * 4 + tq) * 2], tag, a, b);
        const float ms = __uint_as_float(a[0]);
        float mh = fmaxf(ms, shx(ms, 1)); mh = fmaxf(mh, shx(mh, 2));
        float L = __uint_as_float(b[0]) * expdiff(ms, mh);
        L += shx(L, 1); L += shx(L, 2);
        if (lane == 0) {
            sm.fscale = __fdividef(expdiff(mc, mh), L);
            mbar_arrive(BAR(B_FREADY));
        }
    }
    __syncwarp();
    mbar_wait_cluster(BAR(B_OX));
    CK(3);

    {
        float y[4][4];
#pragma unroll
        for (int i = 0; i < 4; i++) y[i][0] = y[i][1] = y[i][2] = y[i][3] = 0.f;
#pragma unroll
        for (int k = 0; k < 4; k++) {
            const float4 a = *reinterpret_cast<const float4*>(&sm.ox[0][k * 16 + tq * 4]), b = *reinterpret_cast<const float4*>(&sm.ox[1][k * 16 + tq * 4]);
            const uint32_t b0 = bf_pack(a.x + b.x, a.y + b.y), b1 = bf_pack(a.z + b.z, a.w + b.w);
#pragma unroll
            for (int i = 0; i < 4; i++) mma_bf16(y[i], wof[4 * i + k], b0, b1);
        }
        red_v4(&g_acc1[slot_off], sel4(tq, y[0][0], y[1][0], y[2][0], y[3][0]), sel4(tq, y[0][2], y[1][2], y[2][2], y[3][2]), 1.0f, 0.0f);
    }
    TS(7);
    CK(4);
    if (!ffn) { TS_FLUSH; return; }

    uint4 guf[8], wdf[4];
    {
        const uint32_t ga = ring0 + 3 * TILE + (64 * w + lrow) * 32 + ((lchk ^ ((lane >> 2) & 1)) << 4);
        mbar_wait(BAR(B_G));
#pragma unroll
        for (int k = 0; k < 4; k++) guf[k] = ldsm_t(ga + k * 512);
        mbar_wait(BAR(B_U));
#pragma unroll
        for (int k = 0; k < 4; k++) guf[4 + k] = ldsm_t(ga + 20480 + k * 512);
    }
    TSX(15);
    CK(5);

    float h0, h1;
    {
        const uint32_t want = __float_as_uint((float)NCTA);
        uint4 v;
        int n = 0;
        if (lane == (cta & 31)) {
            do { v = ld_rlx128(&g_acc1[slot_off]); if (++n > SPIN_LIMIT) __trap(); } while (v.z != want);
        }
        __syncwarp();
        CK(6);
        do { v = ld_rlx128(&g_acc1[slot_off]); if (++n > SPIN_LIMIT) __trap(); } while (v.z != want);
        h0 = rbf(x0 + rbf(__uint_as_float(v.x)));
        h1 = rbf(x1 + rbf(__uint_as_float(v.y)));
    }
    TS(8);
    CK(7);
    float z0, z1;
    {
        sm.xn[fpos] = __float_as_uint(h0) >> 16;
        sm.xn[fpos + 2] = __float_as_uint(h1) >> 16;
        __syncwarp();
        float cg[4] = {0.f, 0.f, 0.f, 0.f}, cu[4] = {0.f, 0.f, 0.f, 0.f}, cs[4] = {0.f, 0.f, 0.f, 0.f};
        const uint32_t ones = 0x3f803f80u;
#pragma unroll
        for (int k = 0; k < 4; k++) {
            const uint2 hv = *reinterpret_cast<const uint2*>(&sm.xn[64 * w + 16 * k + tq * 4]);
            const uint32_t b0 = (g & 1) ? ones : hv.x, b1 = (g & 1) ? ones : hv.y;
            mma_bf16(cg, guf[k], b0, b1);
            mma_bf16(cu, guf[4 + k], b0, b1);
            mma_bf16(cs, (g & 1) ? hv.x : ones, 0u, (g & 1) ? hv.y : ones, 0u, b0, b1);
        }
        sm.part[w][tq * 8 + g] = make_float2(sel4(tq, cg[0], cg[2], cu[0], cu[2]), sel4(tq, cg[1], cg[3], cu[1], cu[3]));
        if (lane < 8 && tq == 0) reinterpret_cast<float*>(&sm.part[w][32])[g] = cs[0];
        if (cta == 0 && t == 0) st_rlx32(&g_epoch, tag);
        mbar_wait(BAR(B_D));
#pragma unroll
        for (int i = 0; i < 4; i++) wdf[i] = ldsm_t(ring0 + 3 * TILE + 40960 + w * 2048 + lrow * 128 + (((i * 2 + lchk) ^ (lane & 7)) << 4));
        CK(10);
        bar_sync(1, NCOMP);
        CK(11);
        float raw = 0.f, csum = 0.f, s1 = 0.f, s2 = 0.f;
#pragma unroll
        for (int i = 0; i < 10; i++) {
            const float2 a = sm.part[i][lane], b = sm.part[i][32];
            raw += a.x; csum += a.y; s1 += b.x; s2 += b.y;
        }
        const float mean = s1 * (1.0f / 640.0f);
        const float var = fmaxf(fmaf(-mean, mean, s2 * (1.0f / 640.0f)), 0.f);
        float sq;
        asm("sqrt.approx.f32 %0, %1;" : "=f"(sq) : "f"(rbf(rbf(var) + 1e-5f)));
        const float v = rbf(__fdividef(fmaf(-rbf(mean), csum, raw), rbf(sq)));
        const float vo = shx(v, 16);
        const float gt = lane < 16 ? v : vo, up = lane < 16 ? vo : v;
        const float y2 = -1.5957691216057308f * (gt + 0.044715f * gt * gt * gt);
        const uint32_t act = bf_bits(rbf(__fdividef(gt, 1.0f + expdiff(y2, 0.f))) * up);
        CK(12);
        const uint32_t pw = act | (__shfl_down_sync(0xffffffffu, act, 1) << 16);
        const uint32_t b0 = __shfl_sync(0xffffffffu, pw, 2 * tq), b1 = __shfl_sync(0xffffffffu, pw, 2 * tq + 8);
        float z[4][4];
#pragma unroll
        for (int i = 0; i < 4; i++) {
            z[i][0] = z[i][1] = z[i][2] = z[i][3] = 0.f;
            mma_bf16(z[i], wdf[i], b0, b1);
        }
        z0 = sel4(tq, z[0][0], z[1][0], z[2][0], z[3][0]);
        z1 = sel4(tq, z[0][2], z[1][2], z[2][2], z[3][2]);
    }
    TS(9);
    CK(13);
    const float4 old = atom_v4(&g_acc2[slot_off], z0, z1, 1.0f, 0.0f);
    CK(14);
    CK_FLUSH;
    if (old.z == (float)(NFFN - 1)) {
        out[col] = __float2bfloat16_rn(h0 + rbf(old.x + z0));
        out[col + 8] = __float2bfloat16_rn(h1 + rbf(old.y + z1));
        st_rlx128(&g_acc1[slot_off], make_uint4(0, 0, 0, 0));
    }
    TS(10);
    TS_FLUSH;
}

typedef CUresult (*EncodeTiledFn)(CUtensorMap*, CUtensorMapDataType, cuuint32_t, void*, const cuuint64_t*, const cuuint64_t*,
                                  const cuuint32_t*, const cuuint32_t*, CUtensorMapInterleave, CUtensorMapSwizzle,
                                  CUtensorMapL2promotion, CUtensorMapFloatOOBfill);

}

extern "C" void kernel_launch(void* const* d_in, const int* in_sizes, int n_in, void* d_out, int out_size) {
    (void)in_sizes; (void)n_in; (void)out_size;
    static CUtensorMap qmap, omap, vmap, gmap, umap, dmap;
    static void* key[9];
    bool same = true;
    for (int i = 0; i < 9; i++) same = same && key[i] == d_in[i];
    if (!same) {
        EncodeTiledFn enc = nullptr;
        cudaDriverEntryPointQueryResult qr;
        cudaGetDriverEntryPoint("cuTensorMapEncodeTiled", (void**)&enc, cudaEnableDefault, &qr);
        auto make = [&](CUtensorMap* m, void* base, cuuint64_t d0, cuuint64_t d1, cuuint64_t d2, cuuint64_t s1, cuuint64_t s2,
                        cuuint32_t b0, cuuint32_t b1, cuuint32_t b2, CUtensorMapSwizzle sw) {
            const cuuint64_t gdim[3] = {d0, d1, d2};
            const cuuint64_t gstr[2] = {s1, s2};
            const cuuint32_t box[3] = {b0, b1, b2};
            const cuuint32_t estr[3] = {1, 1, 1};
            CUresult r = enc(m, CU_TENSOR_MAP_DATA_TYPE_BFLOAT16, 3, base, gdim, gstr, box, estr, CU_TENSOR_MAP_INTERLEAVE_NONE,
                             sw, b0 == 64 ? CU_TENSOR_MAP_L2_PROMOTION_L2_128B : CU_TENSOR_MAP_L2_PROMOTION_L2_256B, CU_TENSOR_MAP_FLOAT_OOB_FILL_NONE);
            (void)r;
        };
        make(&qmap, d_in[3], 64, DM, 64, HQ * DH * 2, 128, 64, 160, 2, CU_TENSOR_MAP_SWIZZLE_128B);
        make(&omap, d_in[4], 64, HQ * DH, 10, DM * 2, 128, 64, 64, 5, CU_TENSOR_MAP_SWIZZLE_128B);
        make(&vmap, d_in[2], 64, (cuuint64_t)HQ * SK, 2, DH * 2, 128, 64, 64, 2, CU_TENSOR_MAP_SWIZZLE_128B);
        make(&dmap, d_in[8], 64, DF, 10, DM * 2, 128, 64, 16, 10, CU_TENSOR_MAP_SWIZZLE_128B);
        make(&gmap, d_in[6], DF, 128, 5, DF * 2, DF * 2 * 128, 16, 128, 5, CU_TENSOR_MAP_SWIZZLE_32B);
        make(&umap, d_in[7], DF, 128, 5, DF * 2, DF * 2 * 128, 16, 128, 5, CU_TENSOR_MAP_SWIZZLE_32B);
        cudaFuncSetAttribute(fused_block_kernel, cudaFuncAttributeMaxDynamicSharedMemorySize, (int)sizeof(Smem));
        for (int i = 0; i < 9; i++) key[i] = d_in[i];
    }
    fused_block_kernel<<<NCTA, NTHREADS, sizeof(Smem), cudaStreamPerThread>>>(
        (const __nv_bfloat16*)d_in[0], (const __nv_bfloat16*)d_in[1], (__nv_bfloat16*)d_out, qmap, omap, vmap, gmap, umap, dmap);
}
```

```cpp
#include <cuda_runtime.h>
#include <cuda_bf16.h>
#include <cuda.h>
#include <stdint.h>
#include <stddef.h>

namespace {

constexpr int DM = 640, HQ = 32, DH = 128, SK = 4096, DF = 1728;
constexpr int NCTA = 128;
constexpr int NFFN = DF / 16;
constexpr int NCOMP = 320;
constexpr int NTHREADS = 384;
constexpr int TILE = 16384;
constexpr int NSLOT = 13;
constexpr int SPIN_LIMIT = 1 << 22;

#define NK0 4
#define STAG 100
#define FTH 0
#define FT 9
#define SG 4
#define SSTR 16
#define POLLALL 1
#define ACCMERGE 1
#define PIPE 0
#define CAP 9
#define FSER 0
#define FD 15
#define FU 14
#define FG 14

enum { B_WQ = 0, B_QX = 2, B_K = 3, B_WO = 19, B_V = 20, B_G = 36, B_U, B_D, B_FREADY,
       B_OX = 40,
       B_EWQ = 41, B_EK = 43, B_EV = 59, B_EWO = 66,
       B_ST = 67, B_GU = 68, B_AR = 69, B_ROLE = 70, NBAR = 71 };

struct __align__(1024) Smem {
    uint8_t  ring[NSLOT * TILE];
    float    sc[1024];
    uint32_t p[512];
    uint16_t xn[DM];
    float2   part[10][32];
    uint32_t ox[2][84];
    float    stat[32];
    float    wred[16];
    uint32_t q[DH / 2];
    float2   qp[64];
    float    fscale;
    int      role;
    uint64_t bar[NBAR];
    unsigned long long pts[40];
};

__device__ __align__(256) uint4    g_ml[NCTA * 2];
__device__ __align__(256) uint4    g_epoch;
__device__ __align__(256) uint32_t g_ticket;
__device__ __align__(256) float4   g_acc1[320 * 16];
__device__ __align__(256) float4   g_acc2[320 * 16];
#define TS_DECL
#define TSP(i)
#define TSX(i)
#define PTS(i)
#define TS(i)
#define TS_FLUSH

#define CK_DECL
#define CK(i)
#define CK_FLUSH

__device__ __forceinline__ uint32_t s2u(const void* p) { return (uint32_t)__cvta_generic_to_shared(p); }
__device__ __forceinline__ void mbar_init(uint32_t bar, uint32_t cnt) {
    asm volatile("mbarrier.init.shared::cta.b64 [%0], %1;" ::"r"(bar), "r"(cnt) : "memory");
}
__device__ __forceinline__ void mbar_expect(uint32_t bar, uint32_t bytes) {
    asm volatile("mbarrier.arrive.expect_tx.shared::cta.b64 _, [%0], %1;" ::"r"(bar), "r"(bytes) : "memory");
}
__device__ __forceinline__ void mbar_arrive(uint32_t bar) {
    asm volatile("mbarrier.arrive.shared::cta.b64 _, [%0];" ::"r"(bar) : "memory");
}
__device__ __forceinline__ void mbar_wait(uint32_t bar) {
    asm volatile("{\n .reg .pred p;\n .reg .u32 n;\n mov.u32 n, 0;\n"
                 "W: mbarrier.try_wait.parity.shared::cta.b64 p, [%0], 0;\n @p bra D;\n"
                 " add.u32 n, n, 1;\n setp.lt.u32 p, n, %1;\n @p bra W;\n trap;\n"
                 "D:\n}" ::"r"(bar), "n"(SPIN_LIMIT) : "memory");
}
__device__ __forceinline__ void mbar_wait_cluster(uint32_t bar) {
    asm volatile("{\n .reg .pred p;\n .reg .u32 n;\n mov.u32 n, 0;\n"
                 "W: mbarrier.try_wait.parity.acquire.cluster.shared::cta.b64 p, [%0], 0;\n @p bra D;\n"
                 " add.u32 n, n, 1;\n setp.lt.u32 p, n, %1;\n @p bra W;\n trap;\n"
                 "D:\n}" ::"r"(bar), "n"(SPIN_LIMIT) : "memory");
}
__device__ __forceinline__ bool mbar_test(uint32_t bar) {
    uint32_t ok;
    asm volatile("{\n .reg .pred p;\n mbarrier.test_wait.parity.shared::cta.b64 p, [%1], 0;\n selp.u32 %0, 1, 0, p;\n}"
                 : "=r"(ok) : "r"(bar) : "memory");
    return ok;
}
__device__ __forceinline__ void bulk_load(uint32_t dst, const void* src, uint32_t bytes, uint32_t bar) {
    asm volatile("cp.async.bulk.shared::cluster.global.mbarrier::complete_tx::bytes [%0], [%1], %2, [%3];"
                 ::"r"(dst), "l"(src), "r"(bytes), "r"(bar) : "memory");
}
__device__ __forceinline__ void tma_3d(uint32_t dst, const CUtensorMap* m, int c0, int c1, int c2, uint32_t bar) {
    asm volatile("cp.async.bulk.tensor.3d.shared::cluster.global.mbarrier::complete_tx::bytes [%0], [%1, {%3, %4, %5}], [%2];"
                 ::"r"(dst), "l"(m), "r"(bar), "r"(c0), "r"(c1), "r"(c2) : "memory");
}
__device__ __forceinline__ uint32_t mapa(uint32_t addr, uint32_t rank) {
    uint32_t r;
    asm volatile("mapa.shared::cluster.u32 %0, %1, %2;" : "=r"(r) : "r"(addr), "r"(rank));
    return r;
}
__device__ __forceinline__ void bar_sync(int id, int n) { asm volatile("bar.sync %0, %1;" ::"r"(id), "r"(n) : "memory"); }
__device__ __forceinline__ void mma_bf16(float (&c)[4], uint32_t a0, uint32_t a1, uint32_t a2, uint32_t a3, uint32_t b0, uint32_t b1) {
    asm volatile("mma.sync.aligned.m16n8k16.row.col.f32.bf16.bf16.f32 {%0,%1,%2,%3}, {%4,%5,%6,%7}, {%8,%9}, {%0,%1,%2,%3};"
                 : "+f"(c[0]), "+f"(c[1]), "+f"(c[2]), "+f"(c[3]) : "r"(a0), "r"(a1), "r"(a2), "r"(a3), "r"(b0), "r"(b1));
}
__device__ __forceinline__ void mma_bf16(float (&c)[4], const uint4& a, uint32_t b0, uint32_t b1) { mma_bf16(c, a.x, a.y, a.z, a.w, b0, b1); }
__device__ __forceinline__ uint4 ldsm_t(uint32_t addr) {
    uint4 r;
    asm volatile("ldmatrix.sync.aligned.m8n8.x4.trans.shared.b16 {%0,%1,%2,%3}, [%4];"
                 : "=r"(r.x), "=r"(r.y), "=r"(r.z), "=r"(r.w) : "r"(addr) : "memory");
    return r;
}
__device__ __forceinline__ float lds32(uint32_t a) { float v; asm volatile("ld.shared.f32 %0, [%1];" : "=f"(v) : "r"(a) : "memory"); return v; }
__device__ __forceinline__ uint2 lds64(uint32_t a) { uint2 v; asm volatile("ld.shared.v2.u32 {%0,%1}, [%2];" : "=r"(v.x), "=r"(v.y) : "r"(a) : "memory"); return v; }
__device__ __forceinline__ float2 lds64f(uint32_t a) { float2 v; asm volatile("ld.shared.v2.f32 {%0,%1}, [%2];" : "=f"(v.x), "=f"(v.y) : "r"(a) : "memory"); return v; }
__device__ __forceinline__ float4 lds128f(uint32_t a) {
    float4 v; asm volatile("ld.shared.v4.f32 {%0,%1,%2,%3}, [%4];" : "=f"(v.x), "=f"(v.y), "=f"(v.z), "=f"(v.w) : "r"(a) : "memory"); return v;
}
__device__ __forceinline__ void sts16(uint32_t a, uint32_t v) { asm volatile("st.shared.u16 [%0], %1;" ::"r"(a), "h"((uint16_t)v) : "memory"); }
__device__ __forceinline__ void sts64f(uint32_t a, float x, float y) { asm volatile("st.shared.v2.f32 [%0], {%1,%2};" ::"r"(a), "f"(x), "f"(y) : "memory"); }
__device__ __forceinline__ uint4 ld_rlx128(const void* p) {
    uint4 v;
    asm volatile("ld.relaxed.gpu.global.v4.u32 {%0,%1,%2,%3}, [%4];" : "=r"(v.x), "=r"(v.y), "=r"(v.z), "=r"(v.w) : "l"(p) : "memory");
    return v;
}
__device__ __forceinline__ void st_tagged(void* p, uint32_t a, uint32_t b, uint32_t tag) {
    const uint64_t lo = ((uint64_t)tag << 32) | a, hi = ((uint64_t)tag << 32) | b;
    asm volatile("st.relaxed.gpu.global.v2.b64 [%0], {%1,%2};" ::"l"(p), "l"(lo), "l"(hi) : "memory");
}
__device__ __forceinline__ bool ld_tagged(const void* p, uint32_t tag, uint32_t& a, uint32_t& b) {
    uint64_t lo, hi;
    asm volatile("ld.relaxed.gpu.global.v2.b64 {%0,%1}, [%2];" : "=l"(lo), "=l"(hi) : "l"(p) : "memory");
    a = (uint32_t)lo; b = (uint32_t)hi;
    return (uint32_t)(lo >> 32) == tag && (uint32_t)(hi >> 32) == tag;
}
template <int N, int S0, int S1>
__device__ __forceinline__ void poll(const uint4* p, uint32_t tag, uint32_t (&a)[N], uint32_t (&b)[N]) {
    int n = 0;
#pragma unroll 1
    while (true) {
        bool ok = true;
#pragma unroll
        for (int i = 0; i < N; i++) ok &= ld_tagged(p + (i & 3) * S0 + (i >> 2) * S1, tag, a[i], b[i]);
        if (ok) break;
        if (++n > SPIN_LIMIT) __trap();
        __nanosleep(64);
    }
}
__device__ __forceinline__ void st_rlx128(void* p, uint4 v) {
    asm volatile("st.relaxed.gpu.global.v4.u32 [%0], {%1,%2,%3,%4};" ::"l"(p), "r"(v.x), "r"(v.y), "r"(v.z), "r"(v.w) : "memory");
}
__device__ __forceinline__ void st_rlx32(void* p, uint32_t v) {
    asm volatile("st.relaxed.gpu.global.u32 [%0], %1;" ::"l"(p), "r"(v) : "memory");
}
__device__ __forceinline__ void red_v4(void* p, float a, float b, float c, float d) {
    asm volatile("red.relaxed.gpu.global.add.v4.f32 [%0], {%1,%2,%3,%4};" ::"l"(p), "f"(a), "f"(b), "f"(c), "f"(d) : "memory");
}
__device__ __forceinline__ float4 atom_v4(void* p, float a, float b, float c, float d) {
    float4 r;
    asm volatile("atom.relaxed.gpu.global.add.v4.f32 {%0,%1,%2,%3}, [%4], {%5,%6,%7,%8};"
                 : "=f"(r.x), "=f"(r.y), "=f"(r.z), "=f"(r.w) : "l"(p), "f"(a), "f"(b), "f"(c), "f"(d) : "memory");
    return r;
}
__device__ __forceinline__ float bf_lo(uint32_t v) { return __uint_as_float(v << 16); }
__device__ __forceinline__ float bf_hi(uint32_t v) { return __uint_as_float(v & 0xffff0000u); }
__device__ __forceinline__ uint32_t bf_pack(float lo, float hi) {
    uint32_t r;
    asm("cvt.rn.bf16x2.f32 %0, %1, %2;" : "=r"(r) : "f"(hi), "f"(lo));
    return r;
}
__device__ __forceinline__ uint32_t bf_bits(float v) { return bf_pack(v, 0.f); }
__device__ __forceinline__ float sel4(int t, float a, float b, float c, float d) { return (t & 2) ? ((t & 1) ? d : c) : ((t & 1) ? b : a); }
__device__ __forceinline__ float rbf(float v) { return __uint_as_float(bf_pack(0.f, v)); }
__device__ __forceinline__ float expdiff(float a, float b) {
    float r;
    asm("ex2.approx.ftz.f32 %0, %1;" : "=f"(r) : "f"((a - b) * 1.4426950408889634f));
    return r;
}
__device__ __forceinline__ float shx(float v, int m) { return __shfl_xor_sync(0xffffffffu, v, m); }

__device__ __forceinline__ float2 layernorm2(float a0, float a1, float* stat, int w, int lane) {
    const float piv = __shfl_sync(0xffffffffu, a0, 0);
    const float d0 = a0 - piv, d1 = a1 - piv;
    float s1 = d0 + d1, s2 = d0 * d0 + d1 * d1;
#pragma unroll
    for (int o = 16; o > 0; o >>= 1) { s1 += shx(s1, o); s2 += shx(s2, o); }
    if (lane == 0) {
        const float mu = s1 * (1.0f / 64.0f);
        *reinterpret_cast<float2*>(stat + 2 * w) = make_float2(piv + mu, fmaxf(s2 - s1 * mu, 0.0f));
    }
    bar_sync(1, NCOMP);
    float mw[10], ms = 0.f, m2 = 0.f;
#pragma unroll
    for (int i = 0; i < 5; i++) {
        const float4 v = *reinterpret_cast<const float4*>(stat + 4 * i);
        mw[2 * i] = v.x; mw[2 * i + 1] = v.z;
        ms += v.x + v.z; m2 += v.y + v.w;
    }
    const float mean = ms * 0.1f;
    float dv = 0.f;
#pragma unroll
    for (int i = 0; i < 10; i++) { const float d = mw[i] - mean; dv = fmaf(d, d, dv); }
    const float var = (m2 + 64.0f * dv) * (1.0f / 640.0f);
    const float mb = rbf(mean);
    float sq;
    asm("sqrt.approx.ftz.f32 %0, %1;" : "=f"(sq) : "f"(rbf(rbf(var) + 1e-5f)));
    const float den = rbf(sq);
    return make_float2(__fdividef(rbf(a0 - mb), den), __fdividef(rbf(a1 - mb), den));
}

__global__ void __cluster_dims__(2, 1, 1) __launch_bounds__(NTHREADS, 1)
fused_block_kernel(const __nv_bfloat16* __restrict__ x, const __nv_bfloat16* __restrict__ kc, __nv_bfloat16* __restrict__ out,
                   const __grid_constant__ CUtensorMap qmap, const __grid_constant__ CUtensorMap omap,
                   const __grid_constant__ CUtensorMap vmap, const __grid_constant__ CUtensorMap gmap,
                   const __grid_constant__ CUtensorMap umap, const __grid_constant__ CUtensorMap dmap) {
    extern __shared__ __align__(1024) uint8_t smem_raw[];
    Smem& sm = *reinterpret_cast<Smem*>(smem_raw);
    int t, cta;
    uint32_t ring0;
    asm volatile("mov.u32 %0, %tid.x;" : "=r"(t));
    asm volatile("mov.u32 %0, %ctaid.x;" : "=r"(cta));
    asm volatile("mov.u32 %0, %1;" : "=r"(ring0) : "r"(s2u(smem_raw)));
    const int w = t >> 5, lane = t & 31;
    const int h = cta >> 2, s = cta & 3;
#define SA(member) (ring0 + (uint32_t)offsetof(Smem, member))
#define BAR(i) (SA(bar) + 8 * (i))

    if (w == 10) {
        PTS(0);
        const uint8_t* kp = reinterpret_cast<const uint8_t*>(kc) + (size_t)cta * (16 * TILE);
        if (lane == 0) {
#pragma unroll
            for (int i = 0; i < B_K + 8; i++) mbar_init(BAR(i), 1);
            asm volatile("fence.mbarrier_init.release.cluster;" ::: "memory");
            mbar_expect(BAR(B_WQ), 40960);
            tma_3d(ring0, &qmap, 0, (s & 1) * 320 + (s >> 1) * 160, 2 * h, BAR(B_WQ));
#pragma unroll 1
            for (int i = 0; i < NK0; i++) {
                if (i == 2) {
                    mbar_expect(BAR(B_WQ + 1), 40960);
                    tma_3d(ring0 + 40960, &qmap, 0, (s & 1) * 320 + 160 - (s >> 1) * 160, 2 * h, BAR(B_WQ + 1));
                }
                mbar_expect(BAR(B_K + i), TILE);
                bulk_load(ring0 + (5 + i) * TILE, kp + (size_t)i * TILE, TILE, BAR(B_K + i));
            }
            mbar_expect(BAR(B_QX), 512);
#pragma unroll
            for (int i = B_K + 8; i < NBAR; i++)
                mbar_init(BAR(i), i < B_OX ? 1 : i == B_OX ? 9 : i < B_EK ? 8 : i < B_EV ? 4 : i < B_EWO ? 8 : i < B_AR ? 10 : 1);
            asm volatile("fence.mbarrier_init.release.cluster;" ::: "memory");
            mbar_expect(BAR(B_OX), 256);
        }
        bar_sync(0, NTHREADS);
        asm volatile("barrier.cluster.arrive.relaxed.aligned;" ::: "memory");
        asm volatile("barrier.cluster.wait.aligned;" ::: "memory");
        if (lane == 0) {
            PTS(1);
#pragma unroll 1
            for (int n = NK0; n < 37; n++) {
                if (n < CAP) mbar_wait(BAR(B_WQ + (n >= NK0 + 2)));
                else mbar_wait(BAR(B_K + (n - CAP < 16 ? n - CAP : n - CAP < 21 ? 16 : n - CAP - 4)));
                if (n >= 8) mbar_wait(n < 10 ? BAR(B_EWQ) : n < 13 ? BAR(B_EWQ + 1) : n < 29 ? BAR(B_EK + n - 13) : n < 34 ? BAR(B_EWO) : BAR(B_EV + n - 34));
                const uint32_t dst = ring0 + ((5 + n) % NSLOT) * TILE;
                if (n < 16) {
                    mbar_expect(BAR(B_K + n), TILE);
                    bulk_load(dst, kp + (size_t)n * TILE, TILE, BAR(B_K + n));
                } else if (n <= 20) {
                    if (n == 16) mbar_expect(BAR(B_WO), 81920);
                    tma_3d(dst, &omap, 0, h * 128, (s & 1) * 5 + n - 16, BAR(B_WO));
                } else {
                    mbar_expect(BAR(B_V + n - 21), TILE);
                    tma_3d(dst, &vmap, 0, cta * 1024 + (n - 21) * 64, 0, BAR(B_V + n - 21));
                }
            }
            PTS(2);
            int role = cta - (NCTA - NFFN);
            if (FT >= 0) {
                mbar_wait(BAR(B_V + FT));
                role = (int)(atomicAdd(&g_ticket, 1u) & (NCTA - 1)) - (NCTA - NFFN);
            }
            sm.role = role;
            mbar_arrive(BAR(B_ROLE));
            if (role >= 0) {
                mbar_wait(BAR(B_EV + 6));
                mbar_wait(BAR(B_V + FG));
                if (FTH) {
                    const float* cp = reinterpret_cast<const float*>(&g_acc1[(cta & 127) * 16]) + 2;
                    float c;
                    int n = 0;
                    do {
                        asm volatile("ld.relaxed.gpu.global.f32 %0, [%1];" : "=f"(c) : "l"(cp) : "memory");
                        if (++n > SPIN_LIMIT) __trap();
                    } while (c < (float)FTH);
                }
                mbar_expect(BAR(B_G), 20480);
                tma_3d(ring0 + 3 * TILE, &gmap, role * 16, 0, 0, BAR(B_G));
                if (FSER & 1) mbar_wait(BAR(B_G));
                mbar_wait(BAR(B_V + FU));
                mbar_expect(BAR(B_U), 20480);
                tma_3d(ring0 + 3 * TILE + 20480, &umap, role * 16, 0, 0, BAR(B_U));
                if (FSER & 2) mbar_wait(BAR(B_U));
                mbar_wait(BAR(B_V + FD));
                mbar_expect(BAR(B_D), 20480);
                tma_3d(ring0 + 3 * TILE + 40960, &dmap, 0, role * 16, 0, BAR(B_D));
            }
        }
        return;
    }

    if (w == 11) {
        bar_sync(0, NTHREADS);
        asm volatile("barrier.cluster.arrive.relaxed.aligned;" ::: "memory");
        asm volatile("barrier.cluster.wait.aligned;" ::: "memory");
        if (lane == 0 && PIPE) {
            const uint32_t want = __float_as_uint((float)NCTA);
            const uint32_t* cp = reinterpret_cast<const uint32_t*>(&g_acc1[(cta & 15) * 16]) + 2;
            mbar_wait(BAR(B_ROLE));
            if (sm.role < 0) return;
            mbar_wait_cluster(BAR(B_OX));
            uint32_t c[4];
#pragma unroll
            for (int i = 0; i < 4; i++) {
                asm volatile("ld.relaxed.gpu.global.u32 %0, [%1];" : "=r"(c[i]) : "l"(cp + i * 3 * 1024) : "memory");
                const uint32_t t0 = clock();
                while (clock() - t0 < STAG) {}
            }
            int n = 0;
            while (true) {
#pragma unroll
                for (int i = 0; i < 4; i++) {
                    if (c[i] == want) goto done;
                    asm volatile("ld.relaxed.gpu.global.u32 %0, [%1];" : "=r"(c[i]) : "l"(cp + i * 3 * 1024) : "memory");
                }
                if (++n > SPIN_LIMIT) __trap();
            }
        done:
            mbar_arrive(BAR(B_AR));
        }
        return;
    }

    TS_DECL
    CK_DECL
    TS(0);
    const int g = lane >> 2, tq = lane & 3;
    const int col = 64 * w + 16 * tq + g;
    uint32_t tag;
    asm volatile("ld.relaxed.gpu.global.u32 %0, [%1];" : "=r"(tag) : "l"(&g_epoch) : "memory");
    uint16_t xa, xb;
    asm volatile("ld.global.nc.u16 %0, [%1];" : "=h"(xa) : "l"(x + col));
    asm volatile("ld.global.nc.u16 %0, [%1];" : "=h"(xb) : "l"(x + col + 8));
    if (w == 9 && lane < 5) {
        const CUtensorMap* m = lane == 0 ? &omap : lane == 1 ? &vmap : lane == 2 ? &gmap : lane == 3 ? &umap : &dmap;
        asm volatile("prefetch.tensormap [%0];" ::"l"(m) : "memory");
    }
    const int su = (t & ~31) + ((tq >> 1) << 4) + (g << 1) + (tq & 1);
    const size_t slot_off = (size_t)(su / SG) * SSTR + (su % SG);
    const int pu = ((s & 1) * 10 + w) * 16 + (g << 1) + (tq & 1);
    float4* redp = &g_acc1[(size_t)(pu / SG) * SSTR + (pu % SG)];
    float4* a1p = &g_acc1[slot_off];
    uint16_t* op = reinterpret_cast<uint16_t*>(out) + col;
    uint4* epp = &g_epoch;
    asm volatile("" : "+l"(redp), "+l"(a1p), "+l"(op), "+l"(epp));
    if (!ACCMERGE && cta == NCTA - 1) st_rlx128(&g_acc2[slot_off], make_uint4(0, 0, 0, 0));
    bar_sync(0, NTHREADS);
    asm volatile("barrier.cluster.arrive.relaxed.aligned;" ::: "memory");
    tag += 1u;
    const int fpos = 64 * w + 16 * tq + (g >> 1) * 4 + (g & 1);
    const uint32_t lrow = (lane & 7) + ((lane >> 4) << 3), lchk = (lane >> 3) & 1;
    const float x0 = bf_lo(xa), x1 = bf_lo(xb);
    {
        const float2 xn = layernorm2(x0, x1, sm.stat, w, lane);
        sm.xn[fpos] = bf_bits(xn.x);
        sm.xn[fpos + 2] = bf_bits(xn.y);
        bar_sync(1, NCOMP);
        asm volatile("barrier.cluster.wait.aligned;" ::: "memory");
    }
    const uint32_t aoff = lrow * 128 + ((((w & 3) * 2 + lchk) ^ (lane & 7)) << 4);
    if (w < 8) {
        float c[4] = {0.f, 0.f, 0.f, 0.f};
#pragma unroll 1
        for (int hf = 0; hf < 2; hf++) {
            mbar_wait(BAR(B_WQ + hf));
            const uint16_t* xp = &sm.xn[(s & 1) * 320 + ((s >> 1) ^ hf) * 160 + tq * 4];
#pragma unroll 5
            for (int k = 0; k < 10; k++) {
                const uint4 a = ldsm_t(ring0 + hf * 40960 + (w >> 2) * 20480 + k * 2048 + aoff);
                const uint2 b = *reinterpret_cast<const uint2*>(xp + k * 16);
                mma_bf16(c, a, b.x, b.y);
            }
            if (lane == 0) mbar_arrive(BAR(B_EWQ + hf));
        }
        TS(11);
        if (tq == 0)
            asm volatile("st.async.weak.shared::cluster.mbarrier::complete_tx::bytes.v2.f32 [%0], {%1, %2}, [%3];"
                         ::"r"(mapa(s2u(&sm.qp[w * 8 + g]), (s & 1) ^ 1)), "f"(c[0]), "f"(c[2]), "r"(mapa(BAR(B_QX), (s & 1) ^ 1)) : "memory");
        mbar_wait_cluster(BAR(B_QX));
        if (tq == 0) {
            const float2 o = sm.qp[w * 8 + g];
            uint16_t* qh = reinterpret_cast<uint16_t*>(sm.q) + w * 16 + g;
            qh[0] = bf_bits(c[0] + o.x);
            qh[8] = bf_bits(c[2] + o.y);
        }
        bar_sync(3, 256);
        TS(1);
        float mx = -INFINITY;
        uint4 qf[4];
#pragma unroll
        for (int c = 0; c < 4; c++) qf[c] = *reinterpret_cast<const uint4*>(&sm.q[(c ^ (g & 1)) * 16 + tq * 4]);
#pragma unroll 1
        for (int i = w >> 2; i < 16; i += 2) {
            mbar_wait(BAR(B_K + i));
            const uint8_t* tp = sm.ring + ((5 + i) % NSLOT) * TILE + ((w & 3) * 16 + g) * 256 + tq * 16;
            uint4 ka[4], kb[4];
#pragma unroll
            for (int c = 0; c < 4; c++) {
                ka[c] = *reinterpret_cast<const uint4*>(tp + ((c ^ (g & 1)) * 64));
                kb[c] = *reinterpret_cast<const uint4*>(tp + 2048 + ((c ^ (g & 1)) * 64));
            }
            float c0[4] = {0.f, 0.f, 0.f, 0.f}, c1[4] = {0.f, 0.f, 0.f, 0.f};
#pragma unroll
            for (int c = 0; c < 4; c++) {
                mma_bf16(c0, ka[c].x, kb[c].x, ka[c].y, kb[c].y, qf[c].x, qf[c].y);
                mma_bf16(c1, ka[c].z, kb[c].z, ka[c].w, kb[c].w, qf[c].z, qf[c].w);
            }
            if (lane == 0) mbar_arrive(BAR(B_EK + i));
            const float slo = rbf(rbf((g & 1) ? c0[1] + c1[1] : c0[0] + c1[0]) * 0.08838834764831845f);
            const float shi = rbf(rbf((g & 1) ? c0[3] + c1[3] : c0[2] + c1[2]) * 0.08838834764831845f);
            mx = fmaxf(mx, fmaxf(slo, shi));
            if (tq < 2) sm.sc[i * 64 + (w & 3) * 16 + g + tq * 8] = tq ? shi : slo;
        }
        TS(2);
        mx = fmaxf(mx, shx(mx, 4)); mx = fmaxf(mx, shx(mx, 8)); mx = fmaxf(mx, shx(mx, 16));
        if (lane == 0) sm.wred[w] = mx;
        bar_sync(3, 256);
#pragma unroll
        for (int i = 0; i < 2; i++) {
            const float4 v = *reinterpret_cast<const float4*>(&sm.wred[4 * i]);
            mx = fmaxf(fmaxf(mx, fmaxf(v.x, v.y)), fmaxf(v.z, v.w));
        }
        const float4 sv = *reinterpret_cast<const float4*>(&sm.sc[4 * t]);
        const float e0 = expdiff(sv.x, mx), e1 = expdiff(sv.y, mx), e2 = expdiff(sv.z, mx), e3 = expdiff(sv.w, mx);
        uint32_t* pp = sm.p + (t >> 2) * 8 + (t & 1) * 4 + ((t >> 1) & 1);
        pp[0] = bf_pack(e0, e1);
        pp[2] = bf_pack(e2, e3);
        float sum = (e0 + e1) + (e2 + e3);
#pragma unroll
        for (int o = 16; o > 0; o >>= 1) sum += shx(sum, o);
        if (lane == 0) sm.wred[8 + w] = sum;
        bar_sync(2, 288);
    }
    float mc = 0.f;
    if (w == 8) {
        bar_sync(2, 288);
        float l = sm.wred[8 + (lane & 7)];
        mc = sm.wred[lane & 7];
        mc = fmaxf(mc, shx(mc, 1)); mc = fmaxf(mc, shx(mc, 2)); mc = fmaxf(mc, shx(mc, 4));
        l += shx(l, 1); l += shx(l, 2); l += shx(l, 4);
        if (lane < 2) st_tagged(&g_ml[cta * 2 + lane], __float_as_uint(mc), __float_as_uint(l), tag);
    }
    uint4 wof[16];
    mbar_wait(BAR(B_WO));
#pragma unroll
    for (int i = 0; i < 16; i++)
        wof[i] = ldsm_t(ring0 + (8 + (w >> 1)) * TILE + (i & 7) * 2048 + lrow * 128 + ((((w & 1) * 4 + (i >> 3) * 2 + lchk) ^ (lane & 7)) << 4));
    if (lane == 0) mbar_arrive(BAR(B_EWO));
    if (w < 8) {
        float c0[4] = {0.f, 0.f, 0.f, 0.f}, c1[4] = {0.f, 0.f, 0.f, 0.f};
        float fs = 0.f;
        const uint32_t oa = SA(ox) + (g >> 1) * 80 + w * 8;
        const uint32_t ra = mapa(oa + 336, (s & 1) ^ 1), rb = mapa(BAR(B_OX), (s & 1) ^ 1);
#pragma unroll 1
        for (int v = 0; v < 16; v++) {
            uint2 b[4];
#pragma unroll
            for (int k = 0; k < 4; k++) b[k] = lds64(SA(p) + v * 128 + k * 32 + tq * 8);
            if (v == 15) {
                mbar_wait(BAR(B_FREADY));
                fs = lds32(SA(fscale));
                TS(5);
            }
            mbar_wait(BAR(B_V + v));
            CK(0);
            const uint32_t tp = ring0 + (v % NSLOT) * TILE + (w >> 2) * 8192 + aoff;
            uint4 a[4];
#pragma unroll
            for (int k = 0; k < 4; k++) a[k] = ldsm_t(tp + k * 2048);
            mma_bf16(c0, a[0], b[0].x, b[0].y); mma_bf16(c1, a[1], b[1].x, b[1].y);
            mma_bf16(c0, a[2], b[2].x, b[2].y); mma_bf16(c1, a[3], b[3].x, b[3].y);
            if (lane == 0 && v < 7) mbar_arrive(BAR(B_EV + v));
            if (v == 0) TS(3);
        }
        const uint32_t pk = bf_pack((c0[0] + c1[0]) * fs, (c0[2] + c1[2]) * fs);
        const uint32_t pk2 = __shfl_down_sync(0xffffffffu, pk, 4);
        if ((lane & 7) == 0) {
            const uint32_t w0 = __byte_perm(pk, pk2, 0x5410), w1 = __byte_perm(pk, pk2, 0x7632);
            asm volatile("st.async.weak.shared::cluster.mbarrier::complete_tx::bytes.v2.b32 [%0], {%1, %2}, [%3];" ::"r"(ra), "r"(w0), "r"(w1), "r"(rb) : "memory");
            asm volatile("st.shared.v2.b32 [%0], {%1, %2};" ::"r"(oa), "r"(w0), "r"(w1) : "memory");
        }
        __syncwarp();
        if (lane == 0) mbar_arrive(BAR(B_OX));
        TS(6);
        CK(1);
    } else if (w == 8) {
        uint32_t a[1], b[1];
        mbar_wait(BAR(B_V + 3));
        poll<1, 0, 0>(&g_ml[(h * 4 + tq) * 2], tag, a, b);
        const float ms = __uint_as_float(a[0]);
        float mh = fmaxf(ms, shx(ms, 1)); mh = fmaxf(mh, shx(mh, 2));
        float L = __uint_as_float(b[0]) * expdiff(ms, mh);
        L += shx(L, 1); L += shx(L, 2);
        if (lane == 0) {
            sm.fscale = __fdividef(expdiff(mc, mh), L);
            mbar_arrive(BAR(B_FREADY));
        }
    }
    __syncwarp();
    mbar_wait_cluster(BAR(B_OX));
    CK(3);

    {
        float y[4][4];
#pragma unroll
        for (int i = 0; i < 4; i++) y[i][0] = y[i][1] = y[i][2] = y[i][3] = 0.f;
#pragma unroll
        for (int k = 0; k < 4; k++) {
            const float4 b = lds128f(SA(ox) + (g & 1) * 336 + tq * 80 + k * 16);
            mma_bf16(y[0], wof[2 * k], __float_as_uint(b.x), __float_as_uint(b.y));
            mma_bf16(y[1], wof[8 + 2 * k], __float_as_uint(b.x), __float_as_uint(b.y));
            mma_bf16(y[2], wof[2 * k + 1], __float_as_uint(b.z), __float_as_uint(b.w));
            mma_bf16(y[3], wof[8 + 2 * k + 1], __float_as_uint(b.z), __float_as_uint(b.w));
        }
        const float ya = (tq & 1) ? (y[1][0] + y[1][1]) + (y[3][0] + y[3][1]) : (y[0][0] + y[0][1]) + (y[2][0] + y[2][1]);
        const float yb = (tq & 1) ? (y[1][2] + y[1][3]) + (y[3][2] + y[3][3]) : (y[0][2] + y[0][3]) + (y[2][2] + y[2][3]);
        if (tq < 2) red_v4(redp, ya, yb, 1.0f, 0.0f);
    }
    TS(7);
    CK(4);
    mbar_wait(BAR(B_ROLE));
    const int role = __float_as_int(lds32(SA(role)));
    if (role < 0) { TS_FLUSH; return; }

    uint4 guf[8], wdf[4];
    {
        const uint32_t ga = ring0 + 3 * TILE + (64 * w + lrow) * 32 + ((lchk ^ ((lane >> 2) & 1)) << 4);
        mbar_wait(BAR(B_G));
#pragma unroll
        for (int k = 0; k < 4; k++) guf[k] = ldsm_t(ga + k * 512);
        mbar_wait(BAR(B_U));
#pragma unroll
        for (int k = 0; k < 4; k++) guf[4 + k] = ldsm_t(ga + 20480 + k * 512);
    }
    const uint32_t da = ring0 + 3 * TILE + 40960 + w * 2048 + lrow * 128;
    const bool dearly = __all_sync(0xffffffffu, mbar_test(BAR(B_D)));
    if (dearly) {
#pragma unroll
        for (int i = 0; i < 4; i++) wdf[i] = ldsm_t(da + (((i * 2 + lchk) ^ (lane & 7)) << 4));
    }
    TSX(15);
    CK(5);

    float4* a2p = a1p + SG;
    float h0, h1;
    {
        const uint32_t want = __float_as_uint((float)(NCTA / 2));
        uint4 v;
        int n = 0;
        if (!POLLALL && lane == (cta & 31)) {
            do { v = ld_rlx128(a1p); if (++n > SPIN_LIMIT) __trap(); } while (v.z != want);
        }
        __syncwarp();
        CK(6);
        do { v = ld_rlx128(a1p); if (++n > SPIN_LIMIT) __trap(); } while (v.z != want);
        h0 = rbf(x0 + rbf(__uint_as_float(v.x)));
        h1 = rbf(x1 + rbf(__uint_as_float(v.y)));
    }
    TS(8);
    CK(7);
    float z0, z1;
    {
        sts16(SA(xn) + fpos * 2, __float_as_uint(h0) >> 16);
        sts16(SA(xn) + fpos * 2 + 4, __float_as_uint(h1) >> 16);
        __syncwarp();
        float cg[4] = {0.f, 0.f, 0.f, 0.f}, cu[4] = {0.f, 0.f, 0.f, 0.f};
        const uint32_t ones = 0x3f803f80u;
#pragma unroll
        for (int k = 0; k < 4; k++) {
            const uint2 hv = lds64(SA(xn) + 128 * w + 32 * k + tq * 8);
            const uint32_t b0 = (g & 1) ? ones : hv.x, b1 = (g & 1) ? ones : hv.y;
            mma_bf16(cg, guf[k], b0, b1);
            mma_bf16(cu, guf[4 + k], b0, b1);
        }
        float s1 = h0 + h1, s2 = fmaf(h0, h0, h1 * h1);
#pragma unroll
        for (int o = 16; o > 0; o >>= 1) { s1 += shx(s1, o); s2 += shx(s2, o); }
        if (lane == 0) {
            sts64f(SA(stat) + 8 * w, s1, s2);
            mbar_arrive(BAR(B_ST));
        }
        sts64f(SA(part) + w * 256 + (tq * 8 + g) * 8, sel4(tq, cg[0], cg[2], cu[0], cu[2]), sel4(tq, cg[1], cg[3], cu[1], cu[3]));
        __syncwarp();
        if (lane == 0) mbar_arrive(BAR(B_GU));
        CK(10);
        if (!dearly) {
            mbar_wait(BAR(B_D));
#pragma unroll
            for (int i = 0; i < 4; i++) wdf[i] = ldsm_t(da + (((i * 2 + lchk) ^ (lane & 7)) << 4));
        }
        mbar_wait(BAR(B_ST));
        s1 = 0.f; s2 = 0.f;
#pragma unroll
        for (int i = 0; i < 5; i++) {
            const float4 b = lds128f(SA(stat) + 16 * i);
            s1 += b.x + b.z; s2 += b.y + b.w;
        }
        const float mean = s1 * (1.0f / 640.0f);
        const float var = fmaxf(fmaf(-mean, mean, s2 * (1.0f / 640.0f)), 0.f);
        float sq, rden;
        asm("sqrt.approx.ftz.f32 %0, %1;" : "=f"(sq) : "f"(rbf(rbf(var) + 1e-5f)));
        asm("rcp.approx.ftz.f32 %0, %1;" : "=f"(rden) : "f"(rbf(sq)));
        const float nmb = -rbf(mean);
        mbar_wait(BAR(B_GU));
        CK(11);
        float ra = 0.f, rb = 0.f, ca = 0.f, cb = 0.f;
#pragma unroll
        for (int i = 0; i < 5; i++) {
            const float2 a = lds64f(SA(part) + i * 512 + lane * 8), b = lds64f(SA(part) + i * 512 + 256 + lane * 8);
            ra += a.x; ca += a.y; rb += b.x; cb += b.y;
        }
        const float v = rbf(fmaf(nmb, ca + cb, ra + rb) * rden);
        const float vo = shx(v, 16);
        const float gt = lane < 16 ? v : vo, up = lane < 16 ? vo : v;
        float ex, rc;
        asm("ex2.approx.ftz.f32 %0, %1;" : "=f"(ex) : "f"(gt * fmaf(gt * gt, -0.10294324f, -2.3022082f)));
        asm("rcp.approx.ftz.f32 %0, %1;" : "=f"(rc) : "f"(1.0f + ex));
        const uint32_t act = bf_bits(rbf(gt * rc) * up);
        CK(12);
        const uint32_t pw = act | (__shfl_down_sync(0xffffffffu, act, 1) << 16);
        const uint32_t b0 = __shfl_sync(0xffffffffu, pw, 2 * tq), b1 = __shfl_sync(0xffffffffu, pw, 2 * tq + 8);
        float z[4][4];
#pragma unroll
        for (int i = 0; i < 4; i++) {
            z[i][0] = z[i][1] = z[i][2] = z[i][3] = 0.f;
            mma_bf16(z[i], wdf[i], b0, b1);
        }
        z0 = sel4(tq, z[0][0], z[1][0], z[2][0], z[3][0]);
        z1 = sel4(tq, z[0][2], z[1][2], z[2][2], z[3][2]);
    }
    TS(9);
    CK(13);
    const float4 old = atom_v4(a2p, z0, z1, 1.0f, 0.0f);
    CK(14);
    CK_FLUSH;
    if (role == 0 && t == 0) st_rlx32(epp, tag);
    if (old.z == (float)(NFFN - 1)) {
        const uint32_t r = bf_pack(h0 + rbf(old.x + z0), h1 + rbf(old.y + z1));
        op[0] = (uint16_t)r;
        op[8] = (uint16_t)(r >> 16);
        if (ACCMERGE) st_rlx128(a2p, make_uint4(0, 0, 0, 0));
        st_rlx128(a1p, make_uint4(0, 0, 0, 0));
    }
    TS(10);
    TS_FLUSH;
}

typedef CUresult (*EncodeTiledFn)(CUtensorMap*, CUtensorMapDataType, cuuint32_t, void*, const cuuint64_t*, const cuuint64_t*,
                                  const cuuint32_t*, const cuuint32_t*, CUtensorMapInterleave, CUtensorMapSwizzle,
                                  CUtensorMapL2promotion, CUtensorMapFloatOOBfill);

}

extern "C" void kernel_launch(void* const* d_in, const int* in_sizes, int n_in, void* d_out, int out_size) {
    (void)in_sizes; (void)n_in; (void)out_size;
    static CUtensorMap qmap, omap, vmap, gmap, umap, dmap;
    static void* key[9];
    bool same = true;
    for (int i = 0; i < 9; i++) same = same && key[i] == d_in[i];
    if (!same) {
        EncodeTiledFn enc = nullptr;
        cudaDriverEntryPointQueryResult qr;
        cudaGetDriverEntryPoint("cuTensorMapEncodeTiled", (void**)&enc, cudaEnableDefault, &qr);
        auto make = [&](CUtensorMap* m, void* base, cuuint64_t d0, cuuint64_t d1, cuuint64_t d2, cuuint64_t s1, cuuint64_t s2,
                        cuuint32_t b0, cuuint32_t b1, cuuint32_t b2, CUtensorMapSwizzle sw) {
            const cuuint64_t gdim[3] = {d0, d1, d2};
            const cuuint64_t gstr[2] = {s1, s2};
            const cuuint32_t box[3] = {b0, b1, b2};
            const cuuint32_t estr[3] = {1, 1, 1};
            CUresult r = enc(m, CU_TENSOR_MAP_DATA_TYPE_BFLOAT16, 3, base, gdim, gstr, box, estr, CU_TENSOR_MAP_INTERLEAVE_NONE,
                             sw, b0 == 64 ? CU_TENSOR_MAP_L2_PROMOTION_L2_128B : CU_TENSOR_MAP_L2_PROMOTION_L2_256B, CU_TENSOR_MAP_FLOAT_OOB_FILL_NONE);
            (void)r;
        };
        make(&qmap, d_in[3], 64, DM, 64, HQ * DH * 2, 128, 64, 160, 2, CU_TENSOR_MAP_SWIZZLE_128B);
        make(&omap, d_in[4], 64, HQ * DH, 10, DM * 2, 128, 64, 128, 1, CU_TENSOR_MAP_SWIZZLE_128B);
        make(&vmap, d_in[2], 64, (cuuint64_t)HQ * SK, 2, DH * 2, 128, 64, 64, 2, CU_TENSOR_MAP_SWIZZLE_128B);
        make(&dmap, d_in[8], 64, DF, 10, DM * 2, 128, 64, 16, 10, CU_TENSOR_MAP_SWIZZLE_128B);
        make(&gmap, d_in[6], DF, 128, 5, DF * 2, DF * 2 * 128, 16, 128, 5, CU_TENSOR_MAP_SWIZZLE_32B);
        make(&umap, d_in[7], DF, 128, 5, DF * 2, DF * 2 * 128, 16, 128, 5, CU_TENSOR_MAP_SWIZZLE_32B);
        cudaFuncSetAttribute(fused_block_kernel, cudaFuncAttributeMaxDynamicSharedMemorySize, (int)sizeof(Smem));
        for (int i = 0; i < 9; i++) key[i] = d_in[i];
    }
    fused_block_kernel<<<NCTA, NTHREADS, sizeof(Smem), cudaStreamPerThread>>>(
        (const __nv_bfloat16*)d_in[0], (const __nv_bfloat16*)d_in[1], (__nv_bfloat16*)d_out, qmap, omap, vmap, gmap, umap, dmap);
}
```

```cpp
#include <cuda_runtime.h>
#include <cuda_bf16.h>
#include <cuda.h>
#include <stdint.h>
#include <stddef.h>

namespace {

constexpr int DM = 640, HQ = 32, DH = 128, SK = 4096, DF = 1728;
constexpr int NCTA = 128;
constexpr int NFFN = DF / 16;
constexpr int NCOMP = 320;
constexpr int NTHREADS = 352;
constexpr int TILE = 16384;
constexpr int NSLOT = 13;
constexpr int SPIN_LIMIT = 1 << 21;

constexpr int NK0 = 4;
constexpr int CAP = 9;
constexpr int PACE_NS = 615;
constexpr int ACTW = 7;
constexpr int SG = 4, SSTR = 16;

enum { B_WQ = 0, B_QX = 2, B_K = 3, B_WO = 19, B_V = 20, B_G = 36, B_U, B_D, B_FREADY,
       B_OX = 40,
       B_EWQ = 41, B_EK = 43, B_EV = 59, B_EWO = 66,
       B_AX = 67, NBAR = 68 };

struct __align__(1024) Smem {
    uint8_t  ring[NSLOT * TILE];
    float    sc[1024];
    uint32_t p[512];
    uint16_t xn[DM];
    float2   part[10][32];
    uint32_t ox[2][84];
    float    stat[32];
    float    wred[16];
    uint32_t q[DH / 2];
    float2   qp[64];
    uint32_t act[16];
    float    fscale;
    uint64_t bar[NBAR];
};

__device__ __align__(256) uint4    g_ml[NCTA * 2];
__device__ __align__(256) uint4    g_epoch;
__device__ __align__(256) float4   g_acc1[80 * 16];


__device__ __forceinline__ uint32_t s2u(const void* p) { return (uint32_t)__cvta_generic_to_shared(p); }
__device__ __forceinline__ void mbar_init(uint32_t bar, uint32_t cnt) {
    asm volatile("mbarrier.init.shared::cta.b64 [%0], %1;" ::"r"(bar), "r"(cnt) : "memory");
}
__device__ __forceinline__ void mbar_expect(uint32_t bar, uint32_t bytes) {
    asm volatile("mbarrier.arrive.expect_tx.shared::cta.b64 _, [%0], %1;" ::"r"(bar), "r"(bytes) : "memory");
}
__device__ __forceinline__ void mbar_arrive(uint32_t bar) {
    asm volatile("mbarrier.arrive.shared::cta.b64 _, [%0];" ::"r"(bar) : "memory");
}
__device__ __forceinline__ void mbar_wait(uint32_t bar) {
    asm volatile("{\n .reg .pred p;\n .reg .u32 n;\n mov.u32 n, 0;\n"
                 "W: mbarrier.try_wait.parity.shared::cta.b64 p, [%0], 0;\n @p bra D;\n"
                 " add.u32 n, n, 1;\n setp.lt.u32 p, n, %1;\n @p bra W;\n trap;\n"
                 "D:\n}" ::"r"(bar), "n"(SPIN_LIMIT) : "memory");
}
__device__ __forceinline__ void mbar_wait_cluster(uint32_t bar) {
    asm volatile("{\n .reg .pred p;\n .reg .u32 n;\n mov.u32 n, 0;\n"
                 "W: mbarrier.try_wait.parity.acquire.cluster.shared::cta.b64 p, [%0], 0;\n @p bra D;\n"
                 " add.u32 n, n, 1;\n setp.lt.u32 p, n, %1;\n @p bra W;\n trap;\n"
                 "D:\n}" ::"r"(bar), "n"(SPIN_LIMIT) : "memory");
}
__device__ __forceinline__ bool mbar_test(uint32_t bar) {
    uint32_t ok;
    asm volatile("{\n .reg .pred p;\n mbarrier.test_wait.parity.shared::cta.b64 p, [%1], 0;\n selp.u32 %0, 1, 0, p;\n}"
                 : "=r"(ok) : "r"(bar) : "memory");
    return ok;
}
__device__ __forceinline__ void bulk_load(uint32_t dst, const void* src, uint32_t bytes, uint32_t bar) {
    asm volatile("cp.async.bulk.shared::cluster.global.mbarrier::complete_tx::bytes [%0], [%1], %2, [%3];"
                 ::"r"(dst), "l"(src), "r"(bytes), "r"(bar) : "memory");
}
__device__ __forceinline__ void tma_3d(uint32_t dst, const CUtensorMap* m, int c0, int c1, int c2, uint32_t bar) {
    asm volatile("cp.async.bulk.tensor.3d.shared::cluster.global.mbarrier::complete_tx::bytes [%0], [%1, {%3, %4, %5}], [%2];"
                 ::"r"(dst), "l"(m), "r"(bar), "r"(c0), "r"(c1), "r"(c2) : "memory");
}
__device__ __forceinline__ uint32_t mapa(uint32_t addr, uint32_t rank) {
    uint32_t r;
    asm volatile("mapa.shared::cluster.u32 %0, %1, %2;" : "=r"(r) : "r"(addr), "r"(rank));
    return r;
}
__device__ __forceinline__ void bar_sync(int id, int n) { asm volatile("bar.sync %0, %1;" ::"r"(id), "r"(n) : "memory"); }
__device__ __forceinline__ void mma_bf16(float (&c)[4], uint32_t a0, uint32_t a1, uint32_t a2, uint32_t a3, uint32_t b0, uint32_t b1) {
    asm volatile("mma.sync.aligned.m16n8k16.row.col.f32.bf16.bf16.f32 {%0,%1,%2,%3}, {%4,%5,%6,%7}, {%8,%9}, {%0,%1,%2,%3};"
                 : "+f"(c[0]), "+f"(c[1]), "+f"(c[2]), "+f"(c[3]) : "r"(a0), "r"(a1), "r"(a2), "r"(a3), "r"(b0), "r"(b1));
}
__device__ __forceinline__ void mma_bf16(float (&c)[4], const uint4& a, uint32_t b0, uint32_t b1) { mma_bf16(c, a.x, a.y, a.z, a.w, b0, b1); }
__device__ __forceinline__ uint4 ldsm_t(uint32_t addr) {
    uint4 r;
    asm volatile("ldmatrix.sync.aligned.m8n8.x4.trans.shared.b16 {%0,%1,%2,%3}, [%4];"
                 : "=r"(r.x), "=r"(r.y), "=r"(r.z), "=r"(r.w) : "r"(addr) : "memory");
    return r;
}
__device__ __forceinline__ float lds32(uint32_t a) { float v; asm volatile("ld.shared.f32 %0, [%1];" : "=f"(v) : "r"(a) : "memory"); return v; }
__device__ __forceinline__ uint2 lds64(uint32_t a) { uint2 v; asm volatile("ld.shared.v2.u32 {%0,%1}, [%2];" : "=r"(v.x), "=r"(v.y) : "r"(a) : "memory"); return v; }
__device__ __forceinline__ float2 lds64f(uint32_t a) { float2 v; asm volatile("ld.shared.v2.f32 {%0,%1}, [%2];" : "=f"(v.x), "=f"(v.y) : "r"(a) : "memory"); return v; }
__device__ __forceinline__ float4 lds128f(uint32_t a) {
    float4 v; asm volatile("ld.shared.v4.f32 {%0,%1,%2,%3}, [%4];" : "=f"(v.x), "=f"(v.y), "=f"(v.z), "=f"(v.w) : "r"(a) : "memory"); return v;
}
__device__ __forceinline__ void sts16(uint32_t a, uint32_t v) { asm volatile("st.shared.u16 [%0], %1;" ::"r"(a), "h"((uint16_t)v) : "memory"); }
__device__ __forceinline__ void sts64f(uint32_t a, float x, float y) { asm volatile("st.shared.v2.f32 [%0], {%1,%2};" ::"r"(a), "f"(x), "f"(y) : "memory"); }
__device__ __forceinline__ uint4 ld_rlx128(const void* p) {
    uint4 v;
    asm volatile("ld.relaxed.gpu.global.v4.u32 {%0,%1,%2,%3}, [%4];" : "=r"(v.x), "=r"(v.y), "=r"(v.z), "=r"(v.w) : "l"(p) : "memory");
    return v;
}
__device__ __forceinline__ void st_tagged(void* p, uint32_t a, uint32_t b, uint32_t tag) {
    const uint64_t lo = ((uint64_t)tag << 32) | a, hi = ((uint64_t)tag << 32) | b;
    asm volatile("st.relaxed.gpu.global.v2.b64 [%0], {%1,%2};" ::"l"(p), "l"(lo), "l"(hi) : "memory");
}
__device__ __forceinline__ bool ld_tagged(const void* p, uint32_t tag, uint32_t& a, uint32_t& b) {
    uint64_t lo, hi;
    asm volatile("ld.relaxed.gpu.global.v2.b64 {%0,%1}, [%2];" : "=l"(lo), "=l"(hi) : "l"(p) : "memory");
    a = (uint32_t)lo; b = (uint32_t)hi;
    return (uint32_t)(lo >> 32) == tag && (uint32_t)(hi >> 32) == tag;
}
template <int N, int S0, int S1>
__device__ __forceinline__ void poll(const uint4* p, uint32_t tag, uint32_t (&a)[N], uint32_t (&b)[N]) {
    int n = 0;
#pragma unroll 1
    while (true) {
        bool ok = true;
#pragma unroll
        for (int i = 0; i < N; i++) ok &= ld_tagged(p + (i & 3) * S0 + (i >> 2) * S1, tag, a[i], b[i]);
        if (ok) break;
        if (++n > SPIN_LIMIT) __trap();
        __nanosleep(64);
    }
}
__device__ __forceinline__ void st_rlx128(void* p, uint4 v) {
    asm volatile("st.relaxed.gpu.global.v4.u32 [%0], {%1,%2,%3,%4};" ::"l"(p), "r"(v.x), "r"(v.y), "r"(v.z), "r"(v.w) : "memory");
}
__device__ __forceinline__ void st_rlx32(void* p, uint32_t v) {
    asm volatile("st.relaxed.gpu.global.u32 [%0], %1;" ::"l"(p), "r"(v) : "memory");
}
__device__ __forceinline__ void red_v4(void* p, float a, float b, float c, float d) {
    asm volatile("red.relaxed.gpu.global.add.v4.f32 [%0], {%1,%2,%3,%4};" ::"l"(p), "f"(a), "f"(b), "f"(c), "f"(d) : "memory");
}
__device__ __forceinline__ float4 atom_v4(void* p, float a, float b, float c, float d) {
    float4 r;
    asm volatile("atom.relaxed.gpu.global.add.v4.f32 {%0,%1,%2,%3}, [%4], {%5,%6,%7,%8};"
                 : "=f"(r.x), "=f"(r.y), "=f"(r.z), "=f"(r.w) : "l"(p), "f"(a), "f"(b), "f"(c), "f"(d) : "memory");
    return r;
}
__device__ __forceinline__ float bf_lo(uint32_t v) { return __uint_as_float(v << 16); }
__device__ __forceinline__ uint32_t bf_pack(float lo, float hi) {
    uint32_t r;
    asm("cvt.rn.bf16x2.f32 %0, %1, %2;" : "=r"(r) : "f"(hi), "f"(lo));
    return r;
}
__device__ __forceinline__ uint32_t bf_bits(float v) { return bf_pack(v, 0.f); }
__device__ __forceinline__ float sel4(int t, float a, float b, float c, float d) { return (t & 2) ? ((t & 1) ? d : c) : ((t & 1) ? b : a); }
__device__ __forceinline__ float rbf(float v) { return __uint_as_float(bf_pack(0.f, v)); }
__device__ __forceinline__ float expdiff(float a, float b) {
    float r;
    asm("ex2.approx.ftz.f32 %0, %1;" : "=f"(r) : "f"((a - b) * 1.4426950408889634f));
    return r;
}
__device__ __forceinline__ float shx(float v, int m) { return __shfl_xor_sync(0xffffffffu, v, m); }

__device__ __forceinline__ float2 layernorm2(float a0, float a1, float* stat, int w, int lane) {
    const float piv = __shfl_sync(0xffffffffu, a0, 0);
    const float d0 = a0 - piv, d1 = a1 - piv;
    float s1 = d0 + d1, s2 = d0 * d0 + d1 * d1;
#pragma unroll
    for (int o = 16; o > 0; o >>= 1) { s1 += shx(s1, o); s2 += shx(s2, o); }
    if (lane == 0) {
        const float mu = s1 * (1.0f / 64.0f);
        *reinterpret_cast<float2*>(stat + 2 * w) = make_float2(piv + mu, fmaxf(s2 - s1 * mu, 0.0f));
    }
    bar_sync(1, NCOMP);
    float mw[10], ms = 0.f, m2 = 0.f;
#pragma unroll
    for (int i = 0; i < 5; i++) {
        const float4 v = *reinterpret_cast<const float4*>(stat + 4 * i);
        mw[2 * i] = v.x; mw[2 * i + 1] = v.z;
        ms += v.x + v.z; m2 += v.y + v.w;
    }
    const float mean = ms * 0.1f;
    float dv = 0.f;
#pragma unroll
    for (int i = 0; i < 10; i++) { const float d = mw[i] - mean; dv = fmaf(d, d, dv); }
    const float var = (m2 + 64.0f * dv) * (1.0f / 640.0f);
    const float mb = rbf(mean);
    float sq;
    asm("sqrt.approx.ftz.f32 %0, %1;" : "=f"(sq) : "f"(rbf(rbf(var) + 1e-5f)));
    const float den = rbf(sq);
    return make_float2(__fdividef(rbf(a0 - mb), den), __fdividef(rbf(a1 - mb), den));
}

__global__ void __cluster_dims__(2, 1, 1) __launch_bounds__(NTHREADS, 1)
fused_block_kernel(const __nv_bfloat16* __restrict__ x, const __nv_bfloat16* __restrict__ kc, __nv_bfloat16* __restrict__ out,
                   const __grid_constant__ CUtensorMap qmap, const __grid_constant__ CUtensorMap omap,
                   const __grid_constant__ CUtensorMap vmap, const __grid_constant__ CUtensorMap gmap,
                   const __grid_constant__ CUtensorMap umap, const __grid_constant__ CUtensorMap dmap) {
    extern __shared__ __align__(1024) uint8_t smem_raw[];
    Smem& sm = *reinterpret_cast<Smem*>(smem_raw);
    int t, cta;
    uint32_t ring0;
    asm volatile("mov.u32 %0, %tid.x;" : "=r"(t));
    asm volatile("mov.u32 %0, %ctaid.x;" : "=r"(cta));
    asm volatile("mov.u32 %0, %1;" : "=r"(ring0) : "r"(s2u(smem_raw)));
    const int w = t >> 5, lane = t & 31;
    const int h = cta >> 2, s = cta & 3;
    const bool ffn = cta < NFFN;
#define SA(member) (ring0 + (uint32_t)offsetof(Smem, member))
#define BAR(i) (SA(bar) + 8 * (i))

    if (w == 10) {
        const uint8_t* kp = reinterpret_cast<const uint8_t*>(kc) + (size_t)cta * (16 * TILE);
        if (lane == 0) {
#pragma unroll
            for (int i = 0; i < B_K + 2; i++) mbar_init(BAR(i), 1);
            asm volatile("fence.mbarrier_init.release.cluster;" ::: "memory");
#pragma unroll
            for (int i = 0; i < 2; i++) {
                mbar_expect(BAR(B_K + i), TILE);
                bulk_load(ring0 + (5 + i) * TILE, kp + (size_t)i * TILE, TILE, BAR(B_K + i));
            }
            mbar_expect(BAR(B_WQ), 40960);
            tma_3d(ring0, &qmap, 0, (s & 1) * 320 + (s >> 1) * 160, 2 * h, BAR(B_WQ));
            mbar_expect(BAR(B_QX), 512);
#pragma unroll
            for (int i = B_K + 2; i < NBAR; i++)
                mbar_init(BAR(i), i < B_OX ? 1 : i == B_OX ? 9 : i < B_EK ? 8 : i < B_EV ? 4 : i < B_EWO ? 8 : i == B_EWO ? 10 : 2);
            asm volatile("fence.mbarrier_init.release.cluster;" ::: "memory");
            mbar_expect(BAR(B_OX), 256);
            mbar_expect(BAR(B_AX), 32);
        }
        __syncwarp();
        asm volatile("bar.arrive 0, %0;" ::"n"(NTHREADS) : "memory");
        asm volatile("barrier.cluster.arrive.relaxed.aligned;" ::: "memory");
        if (lane == 0) {
            uint32_t tstart;
            asm volatile("mov.u32 %0, %globaltimer_lo;" : "=r"(tstart));
#pragma unroll 1
            for (int n = 2; n < 37; n++) {
                if (n == 3) {
                    mbar_expect(BAR(B_WQ + 1), 40960);
                    tma_3d(ring0 + 40960, &qmap, 0, (s & 1) * 320 + 160 - (s >> 1) * 160, 2 * h, BAR(B_WQ + 1));
                }
                if (n < NK0) {}
                else if (n < CAP) mbar_wait(BAR(B_WQ + (n >= NK0 + 2)));
                else mbar_wait(BAR(B_K + (n - CAP < 16 ? n - CAP : n - CAP < 21 ? 16 : n - CAP - 4)));
                if (n >= 8) mbar_wait(n < 10 ? BAR(B_EWQ) : n < 13 ? BAR(B_EWQ + 1) : n < 29 ? BAR(B_EK + n - 13) : n < 34 ? BAR(B_EWO) : BAR(B_EV + n - 34));
                uint32_t now;
                do { asm volatile("mov.u32 %0, %globaltimer_lo;" : "=r"(now)); } while ((int)(now - tstart) < (n - 2) * PACE_NS);
                const uint32_t dst = ring0 + ((5 + n) % NSLOT) * TILE;
                if (n < 16) {
                    mbar_expect(BAR(B_K + n), TILE);
                    bulk_load(dst, kp + (size_t)n * TILE, TILE, BAR(B_K + n));
                } else if (n <= 20) {
                    if (n == 16) mbar_expect(BAR(B_WO), 81920);
                    tma_3d(dst, &omap, 0, h * 128, (s & 1) * 5 + n - 16, BAR(B_WO));
                } else {
                    mbar_expect(BAR(B_V + n - 21), TILE);
                    tma_3d(dst, &vmap, 0, cta * 1024 + (n - 21) * 64, 0, BAR(B_V + n - 21));
                }
            }
            if (ffn) {
                mbar_wait(BAR(B_EV + 6));
                mbar_wait(BAR(B_V + 14));
                mbar_expect(BAR(B_G), 20480);
                tma_3d(ring0 + 3 * TILE, &gmap, cta * 16, 0, 0, BAR(B_G));
                mbar_expect(BAR(B_U), 20480);
                tma_3d(ring0 + 3 * TILE + 20480, &umap, cta * 16, 0, 0, BAR(B_U));
                mbar_wait(BAR(B_V + 15));
                mbar_expect(BAR(B_D), 20480);
                tma_3d(ring0 + 3 * TILE + 40960, &dmap, 0, (cta >> 1) * 32, (s & 1) * 5, BAR(B_D));
            }
        }
        __syncwarp();
        return;
    }

    const int g = lane >> 2, tq = lane & 3;
    const int col = 64 * w + 16 * tq + g;
    uint32_t tag;
    asm volatile("ld.relaxed.gpu.global.u32 %0, [%1];" : "=r"(tag) : "l"(&g_epoch) : "memory");
    uint16_t xa, xb;
    asm volatile("ld.global.nc.u16 %0, [%1];" : "=h"(xa) : "l"(x + col));
    asm volatile("ld.global.nc.u16 %0, [%1];" : "=h"(xb) : "l"(x + col + 8));
    if (w == 9 && lane < 5) {
        const CUtensorMap* m = lane == 0 ? &omap : lane == 1 ? &vmap : lane == 2 ? &gmap : lane == 3 ? &umap : &dmap;
        asm volatile("prefetch.tensormap [%0];" ::"l"(m) : "memory");
    }
    const int su = (t & ~31) + ((tq >> 1) << 4) + (g << 1) + (tq & 1);
    const size_t slot_off = (size_t)(su / SG) * SSTR + (su % SG);
    const int pu = ((s & 1) * 10 + w) * 16 + (g << 1) + (tq & 1);
    float4* redp = &g_acc1[(size_t)(pu / SG) * SSTR + (pu % SG)];
    float4* a1p = &g_acc1[slot_off];
    uint16_t* op = reinterpret_cast<uint16_t*>(out) + (s & 1) * 320 + 32 * w + 16 * (tq & 1) + g;
    uint4* epp = &g_epoch;
    asm volatile("" : "+l"(redp), "+l"(a1p), "+l"(op), "+l"(epp));
    bar_sync(0, NTHREADS);
    asm volatile("barrier.cluster.arrive.relaxed.aligned;" ::: "memory");
    const int fpos = 64 * w + 16 * tq + (g >> 1) * 4 + (g & 1);
    const uint32_t lrow = (lane & 7) + ((lane >> 4) << 3), lchk = (lane >> 3) & 1;
    const float x0 = bf_lo(xa), x1 = bf_lo(xb);
    {
        const float2 xn = layernorm2(x0, x1, sm.stat, w, lane);
        sm.xn[fpos] = bf_bits(xn.x);
        sm.xn[fpos + 2] = bf_bits(xn.y);
        bar_sync(1, NCOMP);
        asm volatile("barrier.cluster.wait.aligned;" ::: "memory");
    }
    const uint32_t aoff = lrow * 128 + ((((w & 3) * 2 + lchk) ^ (lane & 7)) << 4);
    if (w < 8) {
        float c[4] = {0.f, 0.f, 0.f, 0.f};
#pragma unroll 1
        for (int hf = 0; hf < 2; hf++) {
            mbar_wait(BAR(B_WQ + hf));
            const uint16_t* xp = &sm.xn[(s & 1) * 320 + ((s >> 1) ^ hf) * 160 + tq * 4];
#pragma unroll 5
            for (int k = 0; k < 10; k++) {
                const uint4 a = ldsm_t(ring0 + hf * 40960 + (w >> 2) * 20480 + k * 2048 + aoff);
                const uint2 b = *reinterpret_cast<const uint2*>(xp + k * 16);
                mma_bf16(c, a, b.x, b.y);
            }
            if (lane == 0) mbar_arrive(BAR(B_EWQ + hf));
        }
        if (tq == 0)
            asm volatile("st.async.weak.shared::cluster.mbarrier::complete_tx::bytes.v2.f32 [%0], {%1, %2}, [%3];"
                         ::"r"(mapa(s2u(&sm.qp[w * 8 + g]), (s & 1) ^ 1)), "f"(c[0]), "f"(c[2]), "r"(mapa(BAR(B_QX), (s & 1) ^ 1)) : "memory");
        mbar_wait_cluster(BAR(B_QX));
        if (tq == 0) {
            const float2 o = sm.qp[w * 8 + g];
            uint16_t* qh = reinterpret_cast<uint16_t*>(sm.q) + w * 16 + g;
            qh[0] = bf_bits(c[0] + o.x);
            qh[8] = bf_bits(c[2] + o.y);
        }
        bar_sync(3, 256);
        float mx = -INFINITY;
        uint4 qf[4];
#pragma unroll
        for (int c = 0; c < 4; c++) qf[c] = *reinterpret_cast<const uint4*>(&sm.q[(c ^ (g & 1)) * 16 + tq * 4]);
#pragma unroll 1
        for (int i = w >> 2; i < 16; i += 2) {
            mbar_wait(BAR(B_K + i));
            const uint8_t* tp = sm.ring + ((5 + i) % NSLOT) * TILE + ((w & 3) * 16 + g) * 256 + tq * 16;
            uint4 ka[4], kb[4];
#pragma unroll
            for (int c = 0; c < 4; c++) {
                ka[c] = *reinterpret_cast<const uint4*>(tp + ((c ^ (g & 1)) * 64));
                kb[c] = *reinterpret_cast<const uint4*>(tp + 2048 + ((c ^ (g & 1)) * 64));
            }
            float c0[4] = {0.f, 0.f, 0.f, 0.f}, c1[4] = {0.f, 0.f, 0.f, 0.f};
#pragma unroll
            for (int c = 0; c < 4; c++) {
                mma_bf16(c0, ka[c].x, kb[c].x, ka[c].y, kb[c].y, qf[c].x, qf[c].y);
                mma_bf16(c1, ka[c].z, kb[c].z, ka[c].w, kb[c].w, qf[c].z, qf[c].w);
            }
            if (lane == 0) mbar_arrive(BAR(B_EK + i));
            const float slo = rbf(rbf((g & 1) ? c0[1] + c1[1] : c0[0] + c1[0]) * 0.08838834764831845f);
            const float shi = rbf(rbf((g & 1) ? c0[3] + c1[3] : c0[2] + c1[2]) * 0.08838834764831845f);
            mx = fmaxf(mx, fmaxf(slo, shi));
            if (tq < 2) sm.sc[i * 64 + (w & 3) * 16 + g + tq * 8] = tq ? shi : slo;
        }
        mx = fmaxf(mx, shx(mx, 4)); mx = fmaxf(mx, shx(mx, 8)); mx = fmaxf(mx, shx(mx, 16));
        if (lane == 0) sm.wred[w] = mx;
        bar_sync(3, 256);
#pragma unroll
        for (int i = 0; i < 2; i++) {
            const float4 v = *reinterpret_cast<const float4*>(&sm.wred[4 * i]);
            mx = fmaxf(fmaxf(mx, fmaxf(v.x, v.y)), fmaxf(v.z, v.w));
        }
        const float4 sv = *reinterpret_cast<const float4*>(&sm.sc[4 * t]);
        const float e0 = expdiff(sv.x, mx), e1 = expdiff(sv.y, mx), e2 = expdiff(sv.z, mx), e3 = expdiff(sv.w, mx);
        uint32_t* pp = sm.p + (t >> 2) * 8 + (t & 1) * 4 + ((t >> 1) & 1);
        pp[0] = bf_pack(e0, e1);
        pp[2] = bf_pack(e2, e3);
        float sum = (e0 + e1) + (e2 + e3);
#pragma unroll
        for (int o = 16; o > 0; o >>= 1) sum += shx(sum, o);
        if (lane == 0) sm.wred[8 + w] = sum;
        bar_sync(2, 288);
    }
    float mc = 0.f;
    if (w == 8) {
        bar_sync(2, 288);
        float l = sm.wred[8 + (lane & 7)];
        mc = sm.wred[lane & 7];
        mc = fmaxf(mc, shx(mc, 1)); mc = fmaxf(mc, shx(mc, 2)); mc = fmaxf(mc, shx(mc, 4));
        l += shx(l, 1); l += shx(l, 2); l += shx(l, 4);
        if (lane < 2) st_tagged(&g_ml[cta * 2 + lane], __float_as_uint(mc), __float_as_uint(l), tag + 1u);
    }
    uint4 wof[16];
    mbar_wait(BAR(B_WO));
#pragma unroll
    for (int i = 0; i < 16; i++)
        wof[i] = ldsm_t(ring0 + (8 + (w >> 1)) * TILE + (i & 7) * 2048 + lrow * 128 + ((((w & 1) * 4 + (i >> 3) * 2 + lchk) ^ (lane & 7)) << 4));
    if (lane == 0) mbar_arrive(BAR(B_EWO));
    if (w < 8) {
        float c0[4] = {0.f, 0.f, 0.f, 0.f}, c1[4] = {0.f, 0.f, 0.f, 0.f};
        float fs = 0.f;
        const uint32_t oa = SA(ox) + (g >> 1) * 80 + w * 8;
        const uint32_t ra = mapa(oa + 336, (s & 1) ^ 1), rb = mapa(BAR(B_OX), (s & 1) ^ 1);
#pragma unroll 1
        for (int v = 0; v < 16; v++) {
            uint2 b[4];
#pragma unroll
            for (int k = 0; k < 4; k++) b[k] = lds64(SA(p) + v * 128 + k * 32 + tq * 8);
            if (v == 15) {
                mbar_wait(BAR(B_FREADY));
                fs = lds32(SA(fscale));
            }
            mbar_wait(BAR(B_V + v));
            const uint32_t tp = ring0 + (v % NSLOT) * TILE + (w >> 2) * 8192 + aoff;
            uint4 a[4];
#pragma unroll
            for (int k = 0; k < 4; k++) a[k] = ldsm_t(tp + k * 2048);
            mma_bf16(c0, a[0], b[0].x, b[0].y); mma_bf16(c1, a[1], b[1].x, b[1].y);
            mma_bf16(c0, a[2], b[2].x, b[2].y); mma_bf16(c1, a[3], b[3].x, b[3].y);
            if (lane == 0 && v < 7) mbar_arrive(BAR(B_EV + v));
        }
        const uint32_t pk = bf_pack((c0[0] + c1[0]) * fs, (c0[2] + c1[2]) * fs);
        const uint32_t pk2 = __shfl_down_sync(0xffffffffu, pk, 4);
        if ((lane & 7) == 0) {
            const uint32_t w0 = __byte_perm(pk, pk2, 0x5410), w1 = __byte_perm(pk, pk2, 0x7632);
            asm volatile("st.async.weak.shared::cluster.mbarrier::complete_tx::bytes.v2.b32 [%0], {%1, %2}, [%3];" ::"r"(ra), "r"(w0), "r"(w1), "r"(rb) : "memory");
            asm volatile("st.shared.v2.b32 [%0], {%1, %2};" ::"r"(oa), "r"(w0), "r"(w1) : "memory");
        }
        __syncwarp();
        if (lane == 0) mbar_arrive(BAR(B_OX));
    } else if (w == 8) {
        uint32_t a[1], b[1];
        mbar_wait(BAR(B_V + 3));
        poll<1, 0, 0>(&g_ml[(h * 4 + tq) * 2], tag + 1u, a, b);
        const float ms = __uint_as_float(a[0]);
        float mh = fmaxf(ms, shx(ms, 1)); mh = fmaxf(mh, shx(mh, 2));
        float L = __uint_as_float(b[0]) * expdiff(ms, mh);
        L += shx(L, 1); L += shx(L, 2);
        if (lane == 0) {
            sm.fscale = __fdividef(expdiff(mc, mh), L);
            mbar_arrive(BAR(B_FREADY));
        }
    }
    __syncwarp();
    mbar_wait_cluster(BAR(B_OX));

    {
        float y[4][4];
#pragma unroll
        for (int i = 0; i < 4; i++) y[i][0] = y[i][1] = y[i][2] = y[i][3] = 0.f;
#pragma unroll
        for (int k = 0; k < 4; k++) {
            const float4 b = lds128f(SA(ox) + (g & 1) * 336 + tq * 80 + k * 16);
            mma_bf16(y[0], wof[2 * k], __float_as_uint(b.x), __float_as_uint(b.y));
            mma_bf16(y[1], wof[8 + 2 * k], __float_as_uint(b.x), __float_as_uint(b.y));
            mma_bf16(y[2], wof[2 * k + 1], __float_as_uint(b.z), __float_as_uint(b.w));
            mma_bf16(y[3], wof[8 + 2 * k + 1], __float_as_uint(b.z), __float_as_uint(b.w));
        }
        const float ya = (tq & 1) ? (y[1][0] + y[1][1]) + (y[3][0] + y[3][1]) : (y[0][0] + y[0][1]) + (y[2][0] + y[2][1]);
        const float yb = (tq & 1) ? (y[1][2] + y[1][3]) + (y[3][2] + y[3][3]) : (y[0][2] + y[0][3]) + (y[2][2] + y[2][3]);
        if (tq < 2) red_v4(redp, ya, yb, 1.0f, 0.0f);
    }
    if (!ffn) return;

    uint4 guf[8], wdf[4];
    uint4 v = make_uint4(0, 0, 0, 0);
    {
        const uint32_t ga = ring0 + 3 * TILE + (64 * w + lrow) * 32 + ((lchk ^ ((lane >> 2) & 1)) << 4);
        mbar_wait(BAR(B_G));
#pragma unroll
        for (int k = 0; k < 4; k++) guf[k] = ldsm_t(ga + k * 512);
        mbar_wait(BAR(B_U));
#pragma unroll
        for (int k = 0; k < 4; k++) guf[4 + k] = ldsm_t(ga + 20480 + k * 512);
    }
    const uint32_t da = ring0 + 3 * TILE + 40960 + (w >> 1) * 4096 + lrow * 128;
    const bool dearly = __all_sync(0xffffffffu, mbar_test(BAR(B_D)));
    if (dearly) {
#pragma unroll
        for (int i = 0; i < 4; i++) wdf[i] = ldsm_t(da + (i >> 1) * 2048 + ((((w & 1) * 4 + (i & 1) * 2 + lchk) ^ (lane & 7)) << 4));
    }

    float h0, h1;
    {
        const uint32_t want = __float_as_uint((float)(NCTA / 2));
        int n = 0;
        while (v.z != want) { v = ld_rlx128(a1p); if (++n > SPIN_LIMIT) __trap(); }
        h0 = rbf(x0 + rbf(__uint_as_float(v.x)));
        h1 = rbf(x1 + rbf(__uint_as_float(v.y)));
    }
    float z0, z1;
    {
        sts16(SA(xn) + fpos * 2, __float_as_uint(h0) >> 16);
        sts16(SA(xn) + fpos * 2 + 4, __float_as_uint(h1) >> 16);
        __syncwarp();
        float cg[4] = {0.f, 0.f, 0.f, 0.f}, cu[4] = {0.f, 0.f, 0.f, 0.f};
        const uint32_t ones = 0x3f803f80u;
#pragma unroll
        for (int k = 0; k < 4; k++) {
            const uint2 hv = lds64(SA(xn) + 128 * w + 32 * k + tq * 8);
            const uint32_t b0 = (g & 1) ? ones : hv.x, b1 = (g & 1) ? ones : hv.y;
            mma_bf16(cg, guf[k], b0, b1);
            mma_bf16(cu, guf[4 + k], b0, b1);
        }
        float s1 = h0 + h1, s2 = fmaf(h0, h0, h1 * h1);
#pragma unroll
        for (int o = 16; o > 0; o >>= 1) { s1 += shx(s1, o); s2 += shx(s2, o); }
        if (lane == 0) sts64f(SA(stat) + 8 * w, s1, s2);
        sts64f(SA(part) + w * 256 + (tq * 8 + g) * 8, sel4(tq, cg[0], cg[2], cu[0], cu[2]), sel4(tq, cg[1], cg[3], cu[1], cu[3]));
        if (w == ACTW) {
            bar_sync(1, NCOMP);
            float4 sb[5];
            float2 pa[10];
#pragma unroll
            for (int i = 0; i < 5; i++) sb[i] = lds128f(SA(stat) + 16 * i);
#pragma unroll
            for (int i = 0; i < 10; i++) pa[i] = lds64f(SA(part) + i * 256 + lane * 8);
            s1 = ((sb[0].x + sb[0].z) + (sb[1].x + sb[1].z)) + ((sb[2].x + sb[2].z) + (sb[3].x + sb[3].z)) + (sb[4].x + sb[4].z);
            s2 = ((sb[0].y + sb[0].w) + (sb[1].y + sb[1].w)) + ((sb[2].y + sb[2].w) + (sb[3].y + sb[3].w)) + (sb[4].y + sb[4].w);
            const float mean = s1 * (1.0f / 640.0f);
            const float var = fmaxf(fmaf(-mean, mean, s2 * (1.0f / 640.0f)), 0.f);
            float sq, rden;
            asm("sqrt.approx.ftz.f32 %0, %1;" : "=f"(sq) : "f"(rbf(rbf(var) + 1e-5f)));
            asm("rcp.approx.ftz.f32 %0, %1;" : "=f"(rden) : "f"(rbf(sq)));
            const float raw = ((pa[0].x + pa[1].x) + (pa[2].x + pa[3].x)) + ((pa[4].x + pa[5].x) + (pa[6].x + pa[7].x)) + (pa[8].x + pa[9].x);
            const float csum = ((pa[0].y + pa[1].y) + (pa[2].y + pa[3].y)) + ((pa[4].y + pa[5].y) + (pa[6].y + pa[7].y)) + (pa[8].y + pa[9].y);
            const float gt = rbf(fmaf(-rbf(mean), csum, raw) * rden);
            const float up = shx(gt, 16);
            float ex, rc;
            asm("ex2.approx.ftz.f32 %0, %1;" : "=f"(ex) : "f"(gt * fmaf(gt * gt, -0.10294324f, -2.3022082f)));
            asm("rcp.approx.ftz.f32 %0, %1;" : "=f"(rc) : "f"(1.0f + ex));
            const uint32_t ac = bf_bits(rbf(gt * rc) * up);
            const uint32_t pw = ac | (__shfl_down_sync(0xffffffffu, ac, 1) << 16);
            if (lane < 16 && !(lane & 1)) {
                const uint32_t aa = SA(act) + ((lane & 7) >> 1) * 16 + (s & 1) * 8 + (lane >> 3) * 4;
                asm volatile("st.async.weak.shared::cluster.mbarrier::complete_tx::bytes.b32 [%0], %1, [%2];"
                             ::"r"(mapa(aa, (s & 1) ^ 1)), "r"(pw), "r"(mapa(BAR(B_AX), (s & 1) ^ 1)) : "memory");
                asm volatile("st.shared.b32 [%0], %1;" ::"r"(aa), "r"(pw) : "memory");
            }
            __syncwarp();
            if (lane == 0) mbar_arrive(BAR(B_AX));
        } else {
            asm volatile("bar.arrive 1, %0;" ::"n"(NCOMP) : "memory");
        }
        if (!dearly) {
            mbar_wait(BAR(B_D));
#pragma unroll
            for (int i = 0; i < 4; i++) wdf[i] = ldsm_t(da + (i >> 1) * 2048 + ((((w & 1) * 4 + (i & 1) * 2 + lchk) ^ (lane & 7)) << 4));
        }
        mbar_wait_cluster(BAR(B_AX));
        const float4 ab = lds128f(SA(act) + tq * 16);
        float z[2][4];
#pragma unroll
        for (int i = 0; i < 2; i++) {
            z[i][0] = z[i][1] = z[i][2] = z[i][3] = 0.f;
            mma_bf16(z[i], wdf[i], __float_as_uint(ab.x), __float_as_uint(ab.y));
        }
#pragma unroll
        for (int i = 0; i < 2; i++) mma_bf16(z[i], wdf[2 + i], __float_as_uint(ab.z), __float_as_uint(ab.w));
        z0 = (tq & 1) ? z[1][0] : z[0][0];
        z1 = (tq & 1) ? z[1][2] : z[0][2];
    }
    if (tq < 2) {
        const float4 old = atom_v4(redp + SG, z0, z1, 1.0f, 0.0f);
        uint16_t ha, hb;
        const uint32_t hp = SA(xn) + ((s & 1) * 320 + 32 * w + 16 * tq + (g >> 1) * 4 + (g & 1)) * 2;
        asm volatile("ld.shared.u16 %0, [%1];" : "=h"(ha) : "r"(hp) : "memory");
        asm volatile("ld.shared.u16 %0, [%1];" : "=h"(hb) : "r"(hp + 4) : "memory");
        if (old.z == (float)(NFFN / 2 - 1)) {
            const uint32_t r = bf_pack(bf_lo(ha) + rbf(old.x + z0), bf_lo(hb) + rbf(old.y + z1));
            op[0] = (uint16_t)r;
            op[8] = (uint16_t)(r >> 16);
            st_rlx128(redp + SG, make_uint4(0, 0, 0, 0));
            st_rlx128(redp, make_uint4(0, 0, 0, 0));
        }
    }
    if (cta == 0 && t == 0) st_rlx32(epp, tag + 1u);
}

typedef CUresult (*EncodeTiledFn)(CUtensorMap*, CUtensorMapDataType, cuuint32_t, void*, const cuuint64_t*, const cuuint64_t*,
                                  const cuuint32_t*, const cuuint32_t*, CUtensorMapInterleave, CUtensorMapSwizzle,
                                  CUtensorMapL2promotion, CUtensorMapFloatOOBfill);

}

extern "C" void kernel_launch(void* const* d_in, const int* in_sizes, int n_in, void* d_out, int out_size) {
    (void)in_sizes; (void)n_in; (void)out_size;
    static CUtensorMap qmap, omap, vmap, gmap, umap, dmap;
    static void* key[9];
    bool same = true;
    for (int i = 0; i < 9; i++) same = same && key[i] == d_in[i];
    if (!same) {
        EncodeTiledFn enc = nullptr;
        cudaDriverEntryPointQueryResult qr;
        cudaGetDriverEntryPoint("cuTensorMapEncodeTiled", (void**)&enc, cudaEnableDefault, &qr);
        auto make = [&](CUtensorMap* m, void* base, cuuint64_t d0, cuuint64_t d1, cuuint64_t d2, cuuint64_t s1, cuuint64_t s2,
                        cuuint32_t b0, cuuint32_t b1, cuuint32_t b2, CUtensorMapSwizzle sw) {
            const cuuint64_t gdim[3] = {d0, d1, d2};
            const cuuint64_t gstr[2] = {s1, s2};
            const cuuint32_t box[3] = {b0, b1, b2};
            const cuuint32_t estr[3] = {1, 1, 1};
            CUresult r = enc(m, CU_TENSOR_MAP_DATA_TYPE_BFLOAT16, 3, base, gdim, gstr, box, estr, CU_TENSOR_MAP_INTERLEAVE_NONE,
                             sw, b0 == 64 ? CU_TENSOR_MAP_L2_PROMOTION_NONE : CU_TENSOR_MAP_L2_PROMOTION_L2_128B, CU_TENSOR_MAP_FLOAT_OOB_FILL_NONE);
            (void)r;
        };
        make(&qmap, d_in[3], 64, DM, 64, HQ * DH * 2, 128, 64, 160, 2, CU_TENSOR_MAP_SWIZZLE_128B);
        make(&omap, d_in[4], 64, HQ * DH, 10, DM * 2, 128, 64, 128, 1, CU_TENSOR_MAP_SWIZZLE_128B);
        make(&vmap, d_in[2], 64, (cuuint64_t)HQ * SK, 2, DH * 2, 128, 64, 64, 2, CU_TENSOR_MAP_SWIZZLE_128B);
        make(&dmap, d_in[8], 64, DF, 10, DM * 2, 128, 64, 32, 5, CU_TENSOR_MAP_SWIZZLE_128B);
        make(&gmap, d_in[6], DF, 128, 5, DF * 2, DF * 2 * 128, 16, 128, 5, CU_TENSOR_MAP_SWIZZLE_32B);
        make(&umap, d_in[7], DF, 128, 5, DF * 2, DF * 2 * 128, 16, 128, 5, CU_TENSOR_MAP_SWIZZLE_32B);
        cudaFuncSetAttribute(fused_block_kernel, cudaFuncAttributeMaxDynamicSharedMemorySize, (int)sizeof(Smem));
        for (int i = 0; i < 9; i++) key[i] = d_in[i];
    }
    fused_block_kernel<<<NCTA, NTHREADS, sizeof(Smem), cudaStreamPerThread>>>(
        (const __nv_bfloat16*)d_in[0], (const __nv_bfloat16*)d_in[1], (__nv_bfloat16*)d_out, qmap, omap, vmap, gmap, umap, dmap);
}
```
